```python
import torch

def _softmax(x, axis=-1):
    return torch.softmax(x, dim=axis)
def _gelu(x):
    return torch.nn.functional.gelu(x, approximate="tanh")
def _silu(x):
    return torch.nn.functional.silu(x)
def _sigmoid(x):
    return torch.sigmoid(x)
def _layernorm(x, axis=-1, eps=1e-5):
    m = x.mean(dim=axis, keepdim=True)
    v = x.var(dim=axis, keepdim=True, unbiased=False)
    return (x - m) / torch.sqrt(v + eps)
def _scatter_add(tgt, idx, src, axis=0):
    return tgt.clone().index_add_(axis, idx, src)
def _segment_sum(src, seg, n):
    out = torch.zeros((n,) + src.shape[1:], dtype=src.dtype)
    return out.index_add_(0, seg, src)
def _pad(x, pw):
    flat = tuple(v for pair in reversed(pw) for v in pair)
    return torch.nn.functional.pad(x, flat)

kernel_name = 'gated_mix__linear_kernel_hedgehog__mha_block__prompt'

def setup_inputs():

    _w = (lambda a: (lambda t: t.to(torch.bfloat16) if t.is_floating_point() else t)(torch.as_tensor(a)))
    def _A_setup():
        B, S, D, H = 1, 2048, 1024, 32
        Dh = D // H
        return {
            "x": _w((lambda *s: torch.randn(*s, dtype=torch.bfloat16) * 0.05)(B, S, D)),
            "wqkv": _w((lambda *s: torch.randn(*s, dtype=torch.bfloat16) * 3.2)(D, 3 * D)),
            "w_phi": _w((lambda *s: torch.randn(*s, dtype=torch.bfloat16) * 3.2)(H, Dh, Dh) * (Dh ** -0.5)),
            "wo": _w((lambda *s: torch.randn(*s, dtype=torch.bfloat16) * 1.6)(D, D)),
        }
    _A_in = _A_setup()

    def _B_setup():
        B, S, D, H = 1, 2048, 1024, 32
        return {
            "x": _w((lambda *s: torch.randn(*s, dtype=torch.bfloat16) * 0.05)(B, S, D)),
            "wqkv": _w((lambda *s: torch.randn(*s, dtype=torch.bfloat16) * 3.2)(D, 3 * D)),
            "wo": _w((lambda *s: torch.randn(*s, dtype=torch.bfloat16) * 0.1)(D, D)),
        }
    _B_in = _B_setup()

    return {
        "A_x": _A_in["x"],
        "A_wqkv": _A_in["wqkv"],
        "A_w_phi": _A_in["w_phi"],
        "A_wo": _A_in["wo"],
        "B_x": _B_in["x"],
        "B_wqkv": _B_in["wqkv"],
        "B_wo": _B_in["wo"],
        "gate_w": _w((lambda *s: torch.randn(*s, dtype=torch.bfloat16) * 0.4)(1024) * 16.0),
    }

def reference(A_x, A_wqkv, A_w_phi, A_wo, B_x, B_wqkv, B_wo, gate_w):
    def _A_ref(x, wqkv, w_phi, wo):
        B, S, D = x.shape
        H = 32; Dh = D // H
        qkv = (lambda x, *d: x.permute(*d))((x @ wqkv).reshape(B, S, 3, H, Dh), 2, 0, 3, 1, 4)
        q, k, v = qkv[0], qkv[1], qkv[2]
        pq = torch.einsum("bhsd,hdf->bhsf", q, w_phi)
        pk = torch.einsum("bhsd,hdf->bhsf", k, w_phi)
        phi_q = torch.concatenate([_softmax(pq, axis=-1), _softmax(-pq, axis=-1)], axis=-1)
        phi_k = torch.concatenate([_softmax(pk, axis=-1), _softmax(-pk, axis=-1)], axis=-1)
        kv = torch.einsum("bhsf,bhsd->bhfd", phi_k, v)
        z  = torch.einsum("bhsf->bhf", phi_k)
        num = torch.einsum("bhqf,bhfd->bhqd", phi_q, kv)
        den = torch.einsum("bhqf,bhf->bhq", phi_q, z)[..., None] + 1e-6
        o = num / den
        return (lambda x, *d: x.permute(*d))(o, 0, 2, 1, 3).reshape(B, S, D) @ wo

    def _B_ref(x, wqkv, wo):
        B, S, D = x.shape
        H = 32
        Dh = D // H
        qkv = (lambda x, *d: x.permute(*d))((x @ wqkv).reshape(B, S, 3, H, Dh), 2, 0, 3, 1, 4)
        q, k, v = qkv[0], qkv[1], qkv[2]
        scores = torch.einsum("bhqd,bhkd->bhqk", q, k) * (Dh ** -0.5)
        p = _softmax(scores, axis=-1)
        o = torch.einsum("bhqk,bhkd->bhqd", p, v)
        return (lambda x, *d: x.permute(*d))(o, 0, 2, 1, 3).reshape(B, S, D) @ wo

    x = A_x
    g = _sigmoid((x * gate_w).sum(-1, keepdims=True))
    a = _A_ref(x, A_wqkv, A_w_phi, A_wo)
    b = _B_ref(x, B_wqkv, B_wo)
    return g * a + (1 - g) * b
```

```cpp
#include <cuda_runtime.h>
#include <cuda_bf16.h>
#include <cuda.h>
#include <stdint.h>

typedef __nv_bfloat16 bf16;
#define DEVI __device__ __forceinline__

DEVI uint32_t smem_u32(const void* p){ return (uint32_t)__cvta_generic_to_shared(p); }
DEVI void mbar_init(uint32_t bar, uint32_t cnt){ asm volatile("mbarrier.init.shared::cta.b64 [%0], %1;"::"r"(bar),"r"(cnt):"memory"); }
DEVI void mbar_expect_tx(uint32_t bar, uint32_t bytes){ asm volatile("mbarrier.arrive.expect_tx.shared::cta.b64 _, [%0], %1;"::"r"(bar),"r"(bytes):"memory"); }
DEVI void mbar_arrive(uint32_t bar){ asm volatile("mbarrier.arrive.shared::cta.b64 _, [%0];"::"r"(bar):"memory"); }
DEVI bool mbar_try(uint32_t bar, uint32_t parity){ uint32_t ok;
  asm volatile("{\n.reg .pred p;\nmbarrier.try_wait.parity.shared::cta.b64 p, [%1], %2;\nselp.u32 %0, 1, 0, p;\n}\n":"=r"(ok):"r"(bar),"r"(parity):"memory"); return ok; }
DEVI void mbar_wait(uint32_t bar, uint32_t parity){
  asm volatile("{\n.reg .pred p;\n.reg .u32 c;\nmov.u32 c, 0;\nLAB_WAIT:\nmbarrier.try_wait.parity.shared::cta.b64 p, [%0], %1;\n@p bra DONE;\nadd.u32 c, c, 1;\nsetp.lt.u32 p, c, 0x200000;\n@p bra LAB_WAIT;\ntrap;\nDONE:\n}\n"::"r"(bar),"r"(parity):"memory"); }
DEVI void tma2d(uint32_t dst, const CUtensorMap* m, int c0, int c1, uint32_t bar){
  asm volatile("cp.async.bulk.tensor.2d.shared::cluster.global.mbarrier::complete_tx::bytes [%0], [%1, {%3, %4}], [%2];"::"r"(dst),"l"(m),"r"(bar),"r"(c0),"r"(c1):"memory"); }
DEVI void tma3d(uint32_t dst, const CUtensorMap* m, int c0, int c1, int c2, uint32_t bar){
  asm volatile("cp.async.bulk.tensor.3d.shared::cluster.global.mbarrier::complete_tx::bytes [%0], [%1, {%3, %4, %5}], [%2];"::"r"(dst),"l"(m),"r"(bar),"r"(c0),"r"(c1),"r"(c2):"memory"); }
DEVI void tma2d_store(const CUtensorMap* m, uint32_t src, int c0, int c1){
  asm volatile("cp.async.bulk.tensor.2d.global.shared::cta.bulk_group [%0, {%2, %3}], [%1];"::"l"(m),"r"(src),"r"(c0),"r"(c1):"memory"); }
DEVI void bulk_g2s(uint32_t dst, const void* src, uint32_t bytes, uint32_t bar){
  asm volatile("cp.async.bulk.shared::cluster.global.mbarrier::complete_tx::bytes [%0], [%1], %2, [%3];"::"r"(dst),"l"(src),"r"(bytes),"r"(bar):"memory"); }
DEVI void bulk_s2g(void* dst, uint32_t src, uint32_t bytes){
  asm volatile("cp.async.bulk.global.shared::cta.bulk_group [%0], [%1], %2;"::"l"(dst),"r"(src),"r"(bytes):"memory"); }
DEVI void bulk_commit(){ asm volatile("cp.async.bulk.commit_group;":::"memory"); }
template<int N> DEVI void bulk_wait(){ asm volatile("cp.async.bulk.wait_group %0;"::"n"(N):"memory"); }
template<int N> DEVI void bulk_wait_read(){ asm volatile("cp.async.bulk.wait_group.read %0;"::"n"(N):"memory"); }
DEVI void fence_async_smem(){ asm volatile("fence.proxy.async.shared::cta;":::"memory"); }
DEVI void fence_async_all(){ asm volatile("fence.proxy.async;":::"memory"); }
DEVI void wg_fence(){ asm volatile("wgmma.fence.sync.aligned;":::"memory"); }
DEVI void wg_commit(){ asm volatile("wgmma.commit_group.sync.aligned;":::"memory"); }
template<int N> DEVI void wg_wait(){ asm volatile("wgmma.wait_group.sync.aligned %0;"::"n"(N):"memory"); }
DEVI uint64_t mk_desc2(uint32_t lo, uint32_t hi){ uint64_t d; asm("mov.b64 %0, {%1,%2};":"=l"(d):"r"(lo),"r"(hi)); return d; }
template<int R> DEVI void reg_alloc(){ asm volatile("setmaxnreg.inc.sync.aligned.u32 %0;"::"n"(R)); }
template<int R> DEVI void reg_dealloc(){ asm volatile("setmaxnreg.dec.sync.aligned.u32 %0;"::"n"(R)); }
template<int N> DEVI void fence_regs(float (&r)[N]){
  #pragma unroll
  for(int i=0;i<N;i++) asm volatile("":"+f"(r[i])::"memory"); }
DEVI void bar_sync(int id, int n){ asm volatile("bar.sync %0, %1;"::"r"(id),"r"(n):"memory"); }
DEVI void bar_arrive(int id, int n){ asm volatile("bar.arrive %0, %1;"::"r"(id),"r"(n):"memory"); }
DEVI float ex2(float x){ float y; asm("ex2.approx.ftz.f32 %0,%1;":"=f"(y):"f"(x)); return y; }
DEVI float rcp(float x){ float y; asm("rcp.approx.ftz.f32 %0,%1;":"=f"(y):"f"(x)); return y; }
DEVI uint32_t pack(float lo,float hi){ uint32_t y; asm("cvt.rn.bf16x2.f32 %0,%1,%2;":"=r"(y):"f"(hi),"f"(lo)); return y; }
DEVI void stsm4(uint32_t a, uint32_t r0, uint32_t r1, uint32_t r2, uint32_t r3){
  asm volatile("stmatrix.sync.aligned.m8n8.x4.shared.b16 [%0], {%1,%2,%3,%4};"::"r"(a),"r"(r0),"r"(r1),"r"(r2),"r"(r3):"memory"); }
DEVI void flag_add(unsigned* p){ asm volatile("fence.acq_rel.gpu;\nred.relaxed.gpu.global.add.u32 [%0], 1;"::"l"(p):"memory"); }
DEVI void flag_wait(const unsigned* p, unsigned target){
  for(int i=0;i<(1<<22);i++){ unsigned v; asm volatile("ld.acquire.gpu.global.u32 %0, [%1];":"=r"(v):"l"(p):"memory"); if(v>=target) return; __nanosleep(40); }
  asm volatile("trap;"); }
DEVI void red2(float* p, float a, float b){ asm volatile("red.relaxed.gpu.global.add.v2.f32 [%0], {%1,%2};"::"l"(p),"f"(a),"f"(b):"memory"); }
DEVI void red1(float* p, float a){ asm volatile("red.relaxed.gpu.global.add.f32 [%0], %1;"::"l"(p),"f"(a):"memory"); }
#define BOUND(c) asm volatile("{\n.reg .pred p;\nsetp.eq.u32 p, %0, %1;\n@p exit;\n}\n"::"r"(zz),"r"(c):"memory")
template<int TA, int TB> DEVI void wgmma_ss_n192(float (&d)[96], uint64_t da, uint64_t db, int sd){
  asm volatile("{\n.reg .pred p;\nsetp.ne.b32 p, %98, 0;\n"
    "wgmma.mma_async.sync.aligned.m64n192k16.f32.bf16.bf16 {%0, %1, %2, %3, %4, %5, %6, %7, %8, %9, %10, %11, %12, %13, %14, %15, %16, %17, %18, %19, %20, %21, %22, %23, %24, %25, %26, %27, %28, %29, %30, %31, %32, %33, %34, %35, %36, %37, %38, %39, %40, %41, %42, %43, %44, %45, %46, %47, %48, %49, %50, %51, %52, %53, %54, %55, %56, %57, %58, %59, %60, %61, %62, %63, %64, %65, %66, %67, %68, %69, %70, %71, %72, %73, %74, %75, %76, %77, %78, %79, %80, %81, %82, %83, %84, %85, %86, %87, %88, %89, %90, %91, %92, %93, %94, %95}, %96, %97, p, 1, 1, %99, %100;\n}\n"
    : "+f"(d[0]), "+f"(d[1]), "+f"(d[2]), "+f"(d[3]), "+f"(d[4]), "+f"(d[5]), "+f"(d[6]), "+f"(d[7]), "+f"(d[8]), "+f"(d[9]), "+f"(d[10]), "+f"(d[11]), "+f"(d[12]), "+f"(d[13]), "+f"(d[14]), "+f"(d[15]), "+f"(d[16]), "+f"(d[17]), "+f"(d[18]), "+f"(d[19]), "+f"(d[20]), "+f"(d[21]), "+f"(d[22]), "+f"(d[23]), "+f"(d[24]), "+f"(d[25]), "+f"(d[26]), "+f"(d[27]), "+f"(d[28]), "+f"(d[29]), "+f"(d[30]), "+f"(d[31]), "+f"(d[32]), "+f"(d[33]), "+f"(d[34]), "+f"(d[35]), "+f"(d[36]), "+f"(d[37]), "+f"(d[38]), "+f"(d[39]), "+f"(d[40]), "+f"(d[41]), "+f"(d[42]), "+f"(d[43]), "+f"(d[44]), "+f"(d[45]), "+f"(d[46]), "+f"(d[47]), "+f"(d[48]), "+f"(d[49]), "+f"(d[50]), "+f"(d[51]), "+f"(d[52]), "+f"(d[53]), "+f"(d[54]), "+f"(d[55]), "+f"(d[56]), "+f"(d[57]), "+f"(d[58]), "+f"(d[59]), "+f"(d[60]), "+f"(d[61]), "+f"(d[62]), "+f"(d[63]), "+f"(d[64]), "+f"(d[65]), "+f"(d[66]), "+f"(d[67]), "+f"(d[68]), "+f"(d[69]), "+f"(d[70]), "+f"(d[71]), "+f"(d[72]), "+f"(d[73]), "+f"(d[74]), "+f"(d[75]), "+f"(d[76]), "+f"(d[77]), "+f"(d[78]), "+f"(d[79]), "+f"(d[80]), "+f"(d[81]), "+f"(d[82]), "+f"(d[83]), "+f"(d[84]), "+f"(d[85]), "+f"(d[86]), "+f"(d[87]), "+f"(d[88]), "+f"(d[89]), "+f"(d[90]), "+f"(d[91]), "+f"(d[92]), "+f"(d[93]), "+f"(d[94]), "+f"(d[95])
    : "l"(da), "l"(db), "r"(sd), "n"(TA), "n"(TB));
}
template<int TA, int TB> DEVI void wgmma_ss_n128(float (&d)[64], uint64_t da, uint64_t db, int sd){
  asm volatile("{\n.reg .pred p;\nsetp.ne.b32 p, %66, 0;\n"
    "wgmma.mma_async.sync.aligned.m64n128k16.f32.bf16.bf16 {%0, %1, %2, %3, %4, %5, %6, %7, %8, %9, %10, %11, %12, %13, %14, %15, %16, %17, %18, %19, %20, %21, %22, %23, %24, %25, %26, %27, %28, %29, %30, %31, %32, %33, %34, %35, %36, %37, %38, %39, %40, %41, %42, %43, %44, %45, %46, %47, %48, %49, %50, %51, %52, %53, %54, %55, %56, %57, %58, %59, %60, %61, %62, %63}, %64, %65, p, 1, 1, %67, %68;\n}\n"
    : "+f"(d[0]), "+f"(d[1]), "+f"(d[2]), "+f"(d[3]), "+f"(d[4]), "+f"(d[5]), "+f"(d[6]), "+f"(d[7]), "+f"(d[8]), "+f"(d[9]), "+f"(d[10]), "+f"(d[11]), "+f"(d[12]), "+f"(d[13]), "+f"(d[14]), "+f"(d[15]), "+f"(d[16]), "+f"(d[17]), "+f"(d[18]), "+f"(d[19]), "+f"(d[20]), "+f"(d[21]), "+f"(d[22]), "+f"(d[23]), "+f"(d[24]), "+f"(d[25]), "+f"(d[26]), "+f"(d[27]), "+f"(d[28]), "+f"(d[29]), "+f"(d[30]), "+f"(d[31]), "+f"(d[32]), "+f"(d[33]), "+f"(d[34]), "+f"(d[35]), "+f"(d[36]), "+f"(d[37]), "+f"(d[38]), "+f"(d[39]), "+f"(d[40]), "+f"(d[41]), "+f"(d[42]), "+f"(d[43]), "+f"(d[44]), "+f"(d[45]), "+f"(d[46]), "+f"(d[47]), "+f"(d[48]), "+f"(d[49]), "+f"(d[50]), "+f"(d[51]), "+f"(d[52]), "+f"(d[53]), "+f"(d[54]), "+f"(d[55]), "+f"(d[56]), "+f"(d[57]), "+f"(d[58]), "+f"(d[59]), "+f"(d[60]), "+f"(d[61]), "+f"(d[62]), "+f"(d[63])
    : "l"(da), "l"(db), "r"(sd), "n"(TA), "n"(TB));
}
template<int TA, int TB> DEVI void wgmma_ss_n128z(float (&d)[64], uint64_t da, uint64_t db){
  asm volatile("{\n.reg .pred p;\nsetp.ne.b32 p, 0, 0;\n"
    "wgmma.mma_async.sync.aligned.m64n128k16.f32.bf16.bf16 {%0, %1, %2, %3, %4, %5, %6, %7, %8, %9, %10, %11, %12, %13, %14, %15, %16, %17, %18, %19, %20, %21, %22, %23, %24, %25, %26, %27, %28, %29, %30, %31, %32, %33, %34, %35, %36, %37, %38, %39, %40, %41, %42, %43, %44, %45, %46, %47, %48, %49, %50, %51, %52, %53, %54, %55, %56, %57, %58, %59, %60, %61, %62, %63}, %64, %65, p, 1, 1, %66, %67;\n}\n"
    : "=f"(d[0]), "=f"(d[1]), "=f"(d[2]), "=f"(d[3]), "=f"(d[4]), "=f"(d[5]), "=f"(d[6]), "=f"(d[7]), "=f"(d[8]), "=f"(d[9]), "=f"(d[10]), "=f"(d[11]), "=f"(d[12]), "=f"(d[13]), "=f"(d[14]), "=f"(d[15]), "=f"(d[16]), "=f"(d[17]), "=f"(d[18]), "=f"(d[19]), "=f"(d[20]), "=f"(d[21]), "=f"(d[22]), "=f"(d[23]), "=f"(d[24]), "=f"(d[25]), "=f"(d[26]), "=f"(d[27]), "=f"(d[28]), "=f"(d[29]), "=f"(d[30]), "=f"(d[31]), "=f"(d[32]), "=f"(d[33]), "=f"(d[34]), "=f"(d[35]), "=f"(d[36]), "=f"(d[37]), "=f"(d[38]), "=f"(d[39]), "=f"(d[40]), "=f"(d[41]), "=f"(d[42]), "=f"(d[43]), "=f"(d[44]), "=f"(d[45]), "=f"(d[46]), "=f"(d[47]), "=f"(d[48]), "=f"(d[49]), "=f"(d[50]), "=f"(d[51]), "=f"(d[52]), "=f"(d[53]), "=f"(d[54]), "=f"(d[55]), "=f"(d[56]), "=f"(d[57]), "=f"(d[58]), "=f"(d[59]), "=f"(d[60]), "=f"(d[61]), "=f"(d[62]), "=f"(d[63])
    : "l"(da), "l"(db), "n"(TA), "n"(TB));
}
template<int TA, int TB> DEVI void wgmma_ss_n64(float (&d)[32], uint64_t da, uint64_t db, int sd){
  asm volatile("{\n.reg .pred p;\nsetp.ne.b32 p, %34, 0;\n"
    "wgmma.mma_async.sync.aligned.m64n64k16.f32.bf16.bf16 {%0, %1, %2, %3, %4, %5, %6, %7, %8, %9, %10, %11, %12, %13, %14, %15, %16, %17, %18, %19, %20, %21, %22, %23, %24, %25, %26, %27, %28, %29, %30, %31}, %32, %33, p, 1, 1, %35, %36;\n}\n"
    : "+f"(d[0]), "+f"(d[1]), "+f"(d[2]), "+f"(d[3]), "+f"(d[4]), "+f"(d[5]), "+f"(d[6]), "+f"(d[7]), "+f"(d[8]), "+f"(d[9]), "+f"(d[10]), "+f"(d[11]), "+f"(d[12]), "+f"(d[13]), "+f"(d[14]), "+f"(d[15]), "+f"(d[16]), "+f"(d[17]), "+f"(d[18]), "+f"(d[19]), "+f"(d[20]), "+f"(d[21]), "+f"(d[22]), "+f"(d[23]), "+f"(d[24]), "+f"(d[25]), "+f"(d[26]), "+f"(d[27]), "+f"(d[28]), "+f"(d[29]), "+f"(d[30]), "+f"(d[31])
    : "l"(da), "l"(db), "r"(sd), "n"(TA), "n"(TB));
}
template<int TA, int TB> DEVI void wgmma_ss_n64z(float (&d)[32], uint64_t da, uint64_t db){
  asm volatile("{\n.reg .pred p;\nsetp.ne.b32 p, 0, 0;\n"
    "wgmma.mma_async.sync.aligned.m64n64k16.f32.bf16.bf16 {%0, %1, %2, %3, %4, %5, %6, %7, %8, %9, %10, %11, %12, %13, %14, %15, %16, %17, %18, %19, %20, %21, %22, %23, %24, %25, %26, %27, %28, %29, %30, %31}, %32, %33, p, 1, 1, %34, %35;\n}\n"
    : "=f"(d[0]), "=f"(d[1]), "=f"(d[2]), "=f"(d[3]), "=f"(d[4]), "=f"(d[5]), "=f"(d[6]), "=f"(d[7]), "=f"(d[8]), "=f"(d[9]), "=f"(d[10]), "=f"(d[11]), "=f"(d[12]), "=f"(d[13]), "=f"(d[14]), "=f"(d[15]), "=f"(d[16]), "=f"(d[17]), "=f"(d[18]), "=f"(d[19]), "=f"(d[20]), "=f"(d[21]), "=f"(d[22]), "=f"(d[23]), "=f"(d[24]), "=f"(d[25]), "=f"(d[26]), "=f"(d[27]), "=f"(d[28]), "=f"(d[29]), "=f"(d[30]), "=f"(d[31])
    : "l"(da), "l"(db), "n"(TA), "n"(TB));
}
template<int TB> DEVI void wgmma_rs_n40(float (&d)[20], uint32_t a0, uint32_t a1, uint32_t a2, uint32_t a3, uint64_t db, int sd){
  asm volatile("{\n.reg .pred p;\nsetp.ne.b32 p, %25, 0;\n"
    "wgmma.mma_async.sync.aligned.m64n40k16.f32.bf16.bf16 {%0, %1, %2, %3, %4, %5, %6, %7, %8, %9, %10, %11, %12, %13, %14, %15, %16, %17, %18, %19}, {%20,%21,%22,%23}, %24, p, 1, 1, %26;\n}\n"
    : "+f"(d[0]), "+f"(d[1]), "+f"(d[2]), "+f"(d[3]), "+f"(d[4]), "+f"(d[5]), "+f"(d[6]), "+f"(d[7]), "+f"(d[8]), "+f"(d[9]), "+f"(d[10]), "+f"(d[11]), "+f"(d[12]), "+f"(d[13]), "+f"(d[14]), "+f"(d[15]), "+f"(d[16]), "+f"(d[17]), "+f"(d[18]), "+f"(d[19])
    : "r"(a0), "r"(a1), "r"(a2), "r"(a3), "l"(db), "r"(sd), "n"(TB));
}
template<int TB> DEVI void wgmma_rs_n40z(float (&d)[20], uint32_t a0, uint32_t a1, uint32_t a2, uint32_t a3, uint64_t db){
  asm volatile("{\n.reg .pred p;\nsetp.ne.b32 p, 0, 0;\n"
    "wgmma.mma_async.sync.aligned.m64n40k16.f32.bf16.bf16 {%0, %1, %2, %3, %4, %5, %6, %7, %8, %9, %10, %11, %12, %13, %14, %15, %16, %17, %18, %19}, {%20,%21,%22,%23}, %24, p, 1, 1, %25;\n}\n"
    : "=f"(d[0]), "=f"(d[1]), "=f"(d[2]), "=f"(d[3]), "=f"(d[4]), "=f"(d[5]), "=f"(d[6]), "=f"(d[7]), "=f"(d[8]), "=f"(d[9]), "=f"(d[10]), "=f"(d[11]), "=f"(d[12]), "=f"(d[13]), "=f"(d[14]), "=f"(d[15]), "=f"(d[16]), "=f"(d[17]), "=f"(d[18]), "=f"(d[19])
    : "r"(a0), "r"(a1), "r"(a2), "r"(a3), "l"(db), "n"(TB));
}
template<int TA, int TB> DEVI void wgmma_ss_n40(float (&d)[20], uint64_t da, uint64_t db, int sd){
  asm volatile("{\n.reg .pred p;\nsetp.ne.b32 p, %22, 0;\n"
    "wgmma.mma_async.sync.aligned.m64n40k16.f32.bf16.bf16 {%0, %1, %2, %3, %4, %5, %6, %7, %8, %9, %10, %11, %12, %13, %14, %15, %16, %17, %18, %19}, %20, %21, p, 1, 1, %23, %24;\n}\n"
    : "+f"(d[0]), "+f"(d[1]), "+f"(d[2]), "+f"(d[3]), "+f"(d[4]), "+f"(d[5]), "+f"(d[6]), "+f"(d[7]), "+f"(d[8]), "+f"(d[9]), "+f"(d[10]), "+f"(d[11]), "+f"(d[12]), "+f"(d[13]), "+f"(d[14]), "+f"(d[15]), "+f"(d[16]), "+f"(d[17]), "+f"(d[18]), "+f"(d[19])
    : "l"(da), "l"(db), "r"(sd), "n"(TA), "n"(TB));
}
template<int TA, int TB> DEVI void wgmma_ss_n40z(float (&d)[20], uint64_t da, uint64_t db){
  asm volatile("{\n.reg .pred p;\nsetp.ne.b32 p, 0, 0;\n"
    "wgmma.mma_async.sync.aligned.m64n40k16.f32.bf16.bf16 {%0, %1, %2, %3, %4, %5, %6, %7, %8, %9, %10, %11, %12, %13, %14, %15, %16, %17, %18, %19}, %20, %21, p, 1, 1, %22, %23;\n}\n"
    : "=f"(d[0]), "=f"(d[1]), "=f"(d[2]), "=f"(d[3]), "=f"(d[4]), "=f"(d[5]), "=f"(d[6]), "=f"(d[7]), "=f"(d[8]), "=f"(d[9]), "=f"(d[10]), "=f"(d[11]), "=f"(d[12]), "=f"(d[13]), "=f"(d[14]), "=f"(d[15]), "=f"(d[16]), "=f"(d[17]), "=f"(d[18]), "=f"(d[19])
    : "l"(da), "l"(db), "n"(TA), "n"(TB));
}
template<int TB> DEVI void wgmma_rs_n32(float (&d)[16], uint32_t a0, uint32_t a1, uint32_t a2, uint32_t a3, uint64_t db, int sd){
  asm volatile("{\n.reg .pred p;\nsetp.ne.b32 p, %21, 0;\n"
    "wgmma.mma_async.sync.aligned.m64n32k16.f32.bf16.bf16 {%0, %1, %2, %3, %4, %5, %6, %7, %8, %9, %10, %11, %12, %13, %14, %15}, {%16,%17,%18,%19}, %20, p, 1, 1, %22;\n}\n"
    : "+f"(d[0]), "+f"(d[1]), "+f"(d[2]), "+f"(d[3]), "+f"(d[4]), "+f"(d[5]), "+f"(d[6]), "+f"(d[7]), "+f"(d[8]), "+f"(d[9]), "+f"(d[10]), "+f"(d[11]), "+f"(d[12]), "+f"(d[13]), "+f"(d[14]), "+f"(d[15])
    : "r"(a0), "r"(a1), "r"(a2), "r"(a3), "l"(db), "r"(sd), "n"(TB));
}
template<int TB> DEVI void wgmma_rs_n32z(float (&d)[16], uint32_t a0, uint32_t a1, uint32_t a2, uint32_t a3, uint64_t db){
  asm volatile("{\n.reg .pred p;\nsetp.ne.b32 p, 0, 0;\n"
    "wgmma.mma_async.sync.aligned.m64n32k16.f32.bf16.bf16 {%0, %1, %2, %3, %4, %5, %6, %7, %8, %9, %10, %11, %12, %13, %14, %15}, {%16,%17,%18,%19}, %20, p, 1, 1, %21;\n}\n"
    : "=f"(d[0]), "=f"(d[1]), "=f"(d[2]), "=f"(d[3]), "=f"(d[4]), "=f"(d[5]), "=f"(d[6]), "=f"(d[7]), "=f"(d[8]), "=f"(d[9]), "=f"(d[10]), "=f"(d[11]), "=f"(d[12]), "=f"(d[13]), "=f"(d[14]), "=f"(d[15])
    : "r"(a0), "r"(a1), "r"(a2), "r"(a3), "l"(db), "n"(TB));
}

__device__ __align__(1024) bf16 g_q[32*2048*32];
__device__ __align__(1024) bf16 g_kvb[32*16*2*128*32];
__device__ __align__(1024) bf16 g_o[2048*2048];
__device__ __align__(16) float g_kv[32*64*40];
__device__ float g_gate[2048];
__device__ unsigned g_cnt[128];
constexpr int C_KV=0, C_OA=16, C_OB=32;

constexpr float LOG2E = 1.4426950408889634f;
constexpr float SC = 0.17677669529663687f*LOG2E;
constexpr float OFFS = 88.f;
constexpr uint32_t HI64 = (512u>>4)|(2u<<30);
constexpr uint32_t HI128 = (1024u>>4)|(1u<<30);
constexpr uint32_t SB = 1024;

namespace k1 { constexpr int NS=4; constexpr uint32_t ST=40960, STG=SB+NS*ST, BARS=STG+49152, SMEM=NS*ST+49152+256; }
__global__ void __launch_bounds__(384,1) k_qkv(const __grid_constant__ CUtensorMap mx, const __grid_constant__ CUtensorMap mw,
                                               const bf16* __restrict__ x, const bf16* __restrict__ gw){
  using namespace k1;
  extern __shared__ __align__(1024) uint8_t smem_raw[];
  if(smem_u32(smem_raw)!=SB) asm volatile("trap;");
  const int tid=threadIdx.x, lane=tid&31, warp=__shfl_sync(0xffffffffu,tid>>5,0);
  const int m=blockIdx.x&15, hh=blockIdx.x>>4;
  if(tid==0){ for(int s=0;s<NS;s++){ mbar_init(BARS+8*s,1); mbar_init(BARS+64+8*s,8);} asm volatile("fence.mbarrier_init.release.cluster;":::"memory"); }
  __syncthreads();
  asm volatile("griddepcontrol.launch_dependents;");
  if(warp==8){
    if(lane==0){
      int s=0; uint32_t ph=1;
      for(int it=0;it<32;it++){ const int k=(it&15)*64, h0=(it>>4)*16+hh; const uint32_t a=SB+s*ST;
        mbar_wait(BARS+64+8*s,ph); mbar_expect_tx(BARS+8*s,ST);
        tma2d(a,&mx,k,m*128,BARS+8*s);
        tma3d(a+16384,&mw,h0*32,k,0,BARS+8*s);
        tma3d(a+16384+12288,&mw,(h0+8)*32,k,0,BARS+8*s);
        if(++s==NS){s=0;ph^=1;} }
    }
  } else if(warp>8){
    const int w=warp-9;
    if(blockIdx.x==0 && tid-288<128) { for(int i=tid-288;i<128;i+=96) g_cnt[i]=0; }
    for(int i=tid-288;i<640;i+=96) g_kv[blockIdx.x*640+i]=0.f;
    for(int r=w;r<16;r+=3){ const int row=blockIdx.x*16+r; float s=0;
      #pragma unroll
      for(int j=0;j<4;j++){ uint4 a=*(const uint4*)(x+(size_t)row*1024+j*256+lane*8), b=*(const uint4*)(gw+j*256+lane*8);
        const __nv_bfloat162* pa=(const __nv_bfloat162*)&a; const __nv_bfloat162* pb=(const __nv_bfloat162*)&b;
        #pragma unroll
        for(int e=0;e<4;e++){ float2 p=__bfloat1622float2(__hmul2(pa[e],pb[e])); s+=p.x+p.y; } }
      #pragma unroll
      for(int o=16;o;o>>=1) s+=__shfl_xor_sync(0xffffffffu,s,o);
      s=__bfloat162float(__float2bfloat16(s));
      if(lane==0) g_gate[row]=__bfloat162float(__float2bfloat16(1.f/(1.f+__expf(-s)))); }
  } else {
    const int wg=warp>>2;
    float acc[96];
    int s=0, sp=0; uint32_t ph=0;
    for(int t=0;t<2;t++){
      for(int k=0;k<16;k++){
        mbar_wait(BARS+8*s,ph);
        const uint32_t ad=((SB+s*ST+wg*8192)>>4)|(1u<<16), bd=((SB+s*ST+16384)>>4)|((4096u>>4)<<16);
        wg_fence();
        #pragma unroll
        for(int kk=0;kk<4;kk++) wgmma_ss_n192<0,1>(acc,mk_desc2(ad+kk*2,HI128),mk_desc2(bd+kk*64,HI64),(k|kk)!=0);
        wg_commit(); wg_wait<1>();
        if(k>0 && lane==0) mbar_arrive(BARS+64+8*sp);
        sp=s; if(++s==NS){s=0;ph^=1;}
      }
      wg_wait<0>(); fence_regs(acc);
      if(lane==0) mbar_arrive(BARS+64+8*sp);
      if(t==1){ if(tid==0) bulk_wait_read<0>(); bar_sync(1,256); }
      const int row=warp*16+(lane&15);
      #pragma unroll
      for(int c=0;c<12;c++){ const uint32_t a=STG+(c>>1)*8192+row*64+((((c&1)*2+(lane>>4))^((row>>1)&3))<<4);
        stsm4(a,pack(acc[8*c],acc[8*c+1]),pack(acc[8*c+2],acc[8*c+3]),pack(acc[8*c+4],acc[8*c+5]),pack(acc[8*c+6],acc[8*c+7])); }
      fence_async_smem(); bar_sync(1,256);
      if(tid==0){
        #pragma unroll
        for(int j=0;j<2;j++){ const int h=t*16+j*8+hh;
          bulk_s2g(g_q+((size_t)h*2048+m*128)*32, STG+j*24576, 8192);
          bulk_s2g(g_kvb+((size_t)h*16+m)*8192, STG+j*24576+8192, 16384); }
        bulk_commit(); }
    }
    if(tid==0) bulk_wait<0>();
  }
}

#define RAV 144
#define RGV 184
#define GMODE 2
namespace k2 {
  constexpr int NST=4, GST=5;
  constexpr uint32_t SQ=SB, SKV=SQ+32768, SG=SKV+NST*16384, SCR=SG+GST*16384, SW=SCR+32768, SONES=SW+8192, SGATE=SONES+1024, BARS=SGATE+512;
  constexpr uint32_t B_KF=BARS, B_KE=BARS+32, B_Q=BARS+64, B_W=BARS+72, B_GF=BARS+128, B_GE=BARS+192;
  constexpr uint32_t SMEM=BARS+256-SB;
  constexpr int RA=RAV, RG=RGV, RP=512-2*RAV-RGV;
  constexpr int PA=3, PART=10;
}
struct Maps { CUtensorMap x, wa, go, woa, wob, out, wphi; };

DEVI void mnmx(const float (&p)[16], float& x0, float& x1, float& n0, float& n1){
  x0=fmaxf(p[0],p[1]); n0=fminf(p[0],p[1]); x1=fmaxf(p[2],p[3]); n1=fminf(p[2],p[3]);
  #pragma unroll
  for(int j=1;j<4;j++){ x0=fmaxf(x0,fmaxf(p[4*j],p[4*j+1])); n0=fminf(n0,fminf(p[4*j],p[4*j+1])); x1=fmaxf(x1,fmaxf(p[4*j+2],p[4*j+3])); n1=fminf(n1,fminf(p[4*j+2],p[4*j+3])); }
  #pragma unroll
  for(int o=1;o<4;o<<=1){ x0=fmaxf(x0,__shfl_xor_sync(0xffffffffu,x0,o)); x1=fmaxf(x1,__shfl_xor_sync(0xffffffffu,x1,o));
                          n0=fminf(n0,__shfl_xor_sync(0xffffffffu,n0,o)); n1=fminf(n1,__shfl_xor_sync(0xffffffffu,n1,o)); }
}

__global__ void __launch_bounds__(512,1) k_main(const __grid_constant__ Maps mp){
  using namespace k2;
  extern __shared__ __align__(1024) uint8_t smem_raw[];
  if(smem_u32(smem_raw)!=SB) asm volatile("trap;");
  const int tid=threadIdx.x, lane=tid&31, warp=__shfl_sync(0xffffffffu,tid>>5,0);
  const int m=blockIdx.x&15, hh=blockIdx.x>>4;
  if(tid==0){
    for(int s=0;s<NST;s++){ mbar_init(B_KF+8*s,1); mbar_init(B_KE+8*s,8); }
    for(int s=0;s<GST;s++){ mbar_init(B_GF+8*s,1); mbar_init(B_GE+8*s,4); }
    mbar_init(B_Q,1); mbar_init(B_W,1);
    asm volatile("fence.mbarrier_init.release.cluster;":::"memory"); }
  if(tid<256) asm volatile("st.shared.u32 [%0], %1;"::"r"(SONES+tid*4),"r"(0x3F803F80u):"memory");
  fence_async_smem();
  asm volatile("griddepcontrol.wait;":::"memory");
  if(tid>=256 && tid<384) asm volatile("st.shared.f32 [%0], %1;"::"r"(SGATE+(tid-256)*4),"f"(g_gate[m*128+tid-256]):"memory");
  __syncthreads();

  if(warp>=12){
    reg_dealloc<RP>();
    if(warp==12){
      if(lane==0){
        mbar_expect_tx(B_Q,32768);
        for(int r=0;r<4;r++) bulk_g2s(SQ+r*8192, g_q+((size_t)(8*r+hh)*2048+m*128)*32, 8192, B_Q);
        int sl=0; uint32_t ph=1;
        for(int it=0;it<64;it++){ const int h=8*(it>>4)+hh, t=(it+m)&15;
          mbar_wait(B_KE+8*sl,ph); mbar_expect_tx(B_KF+8*sl,16384);
          bulk_g2s(SKV+sl*16384, g_kvb+((size_t)h*16+t)*8192, 16384, B_KF+8*sl);
          if(++sl==NST){sl=0;ph^=1;} }
      }
    } else if(warp==13){
      if(lane==0){
        mbar_expect_tx(B_W,8192); tma2d(SW,&mp.wphi,0,hh*128,B_W);
        int s=0; uint32_t ph=1;
        for(int it=0;it<160;it++){
          const int job=it>>5, k=(it&31)*32; const uint32_t a=SG+s*16384, bar=B_GF+8*s;
          if(it==96){ flag_wait(&g_cnt[C_OA+m],8); fence_async_all(); }
          if(it>=128 && (it&7)==0){ flag_wait(&g_cnt[C_OB+((it-128)>>3)*16+m],8); fence_async_all(); }
          mbar_wait(B_GE+8*s,ph); mbar_expect_tx(bar,16384);
          if(job<3){
            const int n0 = job<2 ? 1024+hh*128+job*64 : hh*128, n1 = job<2 ? n0+1024 : n0+64;
            tma2d(a,&mp.x,k,m*128,bar); tma2d(a+8192,&mp.wa,n0,k,bar); tma2d(a+12288,&mp.wa,n1,k,bar);
          } else {
            const CUtensorMap* wm = job==3 ? &mp.woa : &mp.wob;
            tma2d(a+8192,wm,hh*128,k,bar); tma2d(a+12288,wm,hh*128+64,k,bar); tma2d(a,&mp.go,(job-3)*1024+k,m*128,bar);
          }
          if(++s==GST){s=0;ph^=1;} }
      }
    } else if(warp==14){
      for(int r=0;r<4;r++){ bar_sync(2,288); if(lane==0) flag_add(&g_cnt[C_OB+r*16+m]); __syncwarp(); }
    }
  } else if(warp>=8){
    reg_alloc<RG>();
    const int wq=warp-8, t128=tid-256;
    int s=0; uint32_t ph=0;
    #pragma unroll 1
    for(int job=0;job<4;job++){
      float acc[2][64];
      auto stage=[&](const bool z){
        mbar_wait(B_GF+8*s,ph);
        const uint32_t ad=((SG+s*16384)>>4)|(1u<<16), bd=((SG+s*16384+8192)>>4)|((4096u>>4)<<16);
        #pragma unroll
        for(int kk=0;kk<2;kk++){
          wg_fence();
          if(z&&kk==0) wgmma_ss_n128z<0,1>(acc[0],mk_desc2(ad,HI64),mk_desc2(bd,HI128));
          else wgmma_ss_n128<0,1>(acc[0],mk_desc2(ad+kk*2,HI64),mk_desc2(bd+kk*128,HI128),1);
          if(GMODE==1){ wg_commit(); wg_wait<0>(); wg_fence(); }
          if(z&&kk==0) wgmma_ss_n128z<0,1>(acc[1],mk_desc2(ad+256,HI64),mk_desc2(bd,HI128));
          else wgmma_ss_n128<0,1>(acc[1],mk_desc2(ad+256+kk*2,HI64),mk_desc2(bd+kk*128,HI128),1);
          wg_commit(); wg_wait<0>();
        }
        if(lane==0) mbar_arrive(B_GE+8*s);
        if(++s==GST){s=0;ph^=1;} };
      const int nst = job==3 ? 64 : 32;
      stage(true);
      #pragma unroll 1
      for(int st=1;st<nst;st++) stage(false);
      fence_regs(acc[0]); fence_regs(acc[1]);
      const int srow=wq*16+(lane&15);
      if(job<2){
        if(job==0) mbar_wait(B_W,0);
        uint32_t kf[2][16];
        #pragma unroll
        for(int mb=0;mb<2;mb++){
          #pragma unroll
          for(int i=0;i<16;i++) kf[mb][i]=pack(acc[mb][2*i],acc[mb][2*i+1]);
          const int row=mb*64+srow;
          #pragma unroll
          for(int c=0;c<4;c++){ const float* v=&acc[mb][32+8*c];
            stsm4(SCR+(c>>1)*8192+row*64+((((c&1)*2+(lane>>4))^((row>>1)&3))<<4), pack(v[0],v[1]),pack(v[2],v[3]),pack(v[4],v[5]),pack(v[6],v[7])); }
        }
        float pk[2][2][16];
        wg_fence();
        #pragma unroll
        for(int h=0;h<2;h++){ const uint32_t wd=((SW+(job*2+h)*2048)>>4)|(1u<<16);
          #pragma unroll
          for(int mb=0;mb<2;mb++){
            wgmma_rs_n32z<1>(pk[h][mb],kf[mb][8*h],kf[mb][8*h+1],kf[mb][8*h+2],kf[mb][8*h+3],mk_desc2(wd,HI64));
            wgmma_rs_n32<1>(pk[h][mb],kf[mb][8*h+4],kf[mb][8*h+5],kf[mb][8*h+6],kf[mb][8*h+7],mk_desc2(wd+64,HI64),1); } }
        wg_commit(); wg_wait<0>();
        #pragma unroll
        for(int h=0;h<2;h++){
          fence_regs(pk[h][0]); fence_regs(pk[h][1]);
          uint32_t ph_[2][16];
          #pragma unroll
          for(int mb=0;mb<2;mb++){
            float (&p)[16]=pk[h][mb]; float x0,x1,n0,n1; mnmx(p,x0,x1,n0,n1);
            x0*=-LOG2E; x1*=-LOG2E; n0*=LOG2E; n1*=LOG2E;
            float ep[16],en[16],sp0=0,sp1=0,sn0=0,sn1=0;
            #pragma unroll
            for(int i=0;i<16;i++){ const bool hi=i&2; ep[i]=ex2(fmaf(p[i],LOG2E,hi?x1:x0)); en[i]=ex2(fmaf(p[i],-LOG2E,hi?n1:n0));
              if(hi){ sp1+=ep[i]; sn1+=en[i]; } else { sp0+=ep[i]; sn0+=en[i]; } }
            #pragma unroll
            for(int o=1;o<4;o<<=1){ sp0+=__shfl_xor_sync(0xffffffffu,sp0,o); sp1+=__shfl_xor_sync(0xffffffffu,sp1,o); sn0+=__shfl_xor_sync(0xffffffffu,sn0,o); sn1+=__shfl_xor_sync(0xffffffffu,sn1,o); }
            sp0=rcp(sp0); sp1=rcp(sp1); sn0=rcp(sn0); sn1=rcp(sn1);
            #pragma unroll
            for(int i=0;i<8;i++){ const bool hi=i&1; ph_[mb][i]=pack(ep[2*i]*(hi?sp1:sp0),ep[2*i+1]*(hi?sp1:sp0)); ph_[mb][8+i]=pack(en[2*i]*(hi?sn1:sn0),en[2*i+1]*(hi?sn1:sn0)); }
          }
          if(h==1) bar_sync(1,128);
          #pragma unroll
          for(int mb=0;mb<2;mb++){ const int row=mb*64+srow;
            #pragma unroll
            for(int c=0;c<4;c++) stsm4(SCR+16384+row*128+(((2*c+(lane>>4))^(row&7))<<4), ph_[mb][4*c],ph_[mb][4*c+1],ph_[mb][4*c+2],ph_[mb][4*c+3]); }
          fence_async_smem(); bar_sync(1,128);
          float kv[20];
          const uint32_t pd=((SCR+16384)>>4)|(1u<<16), vd=((SCR+h*8192)>>4)|(((SONES-SCR-h*8192)>>4)<<16);
          wg_fence();
          wgmma_ss_n40z<1,1>(kv,mk_desc2(pd,HI128),mk_desc2(vd,HI64));
          #pragma unroll
          for(int ks=1;ks<8;ks++) wgmma_ss_n40<1,1>(kv,mk_desc2(pd+ks*128,HI128),mk_desc2(vd+ks*(64u-(64u<<16)),HI64),1);
          wg_commit(); wg_wait<0>(); fence_regs(kv);
          float* dst=g_kv+((size_t)(4*hh+2*job+h)*64+wq*16+(lane>>2))*40+(lane&3)*2;
          #pragma unroll
          for(int j=0;j<4;j++){ red2(dst+8*j,kv[4*j],kv[4*j+1]); red2(dst+320+8*j,kv[4*j+2],kv[4*j+3]); }
          if((lane&3)==0){ red1(dst+32,kv[16]); red1(dst+352,kv[18]); }
        }
        bar_sync(1,128);
        if(job==1 && t128==0) flag_add(&g_cnt[C_KV+hh]);
      } else if(job==2){
        uint32_t qf[2][32];
        #pragma unroll
        for(int mb=0;mb<2;mb++){
          #pragma unroll
          for(int i=0;i<32;i++) qf[mb][i]=pack(acc[mb][2*i],acc[mb][2*i+1]); }
        if(t128==0) flag_wait(&g_cnt[C_KV+hh],16);
        bar_sync(1,128);
        #pragma unroll
        for(int i=0;i<8;i++){ const int c=i*128+t128, f=c>>2, ch=c&3;
          const float4* src=(const float4*)(g_kv+((size_t)hh*256+f)*40+ch*8); float4 a=__ldcg(src), b=__ldcg(src+1);
          asm volatile("st.shared.v4.u32 [%0], {%1,%2,%3,%4};"::"r"(SCR+f*64+((ch^((f>>1)&3))<<4)),"r"(pack(a.x,a.y)),"r"(pack(a.z,a.w)),"r"(pack(b.x,b.y)),"r"(pack(b.z,b.w)):"memory"); }
        #pragma unroll
        for(int i=0;i<2;i++){ const int c=i*128+t128, f=c&63, h=c>>6; const float z=__ldcg(g_kv+((size_t)hh*256+c)*40+32);
          asm volatile("st.shared.v4.u32 [%0], {%1,%2,%3,%4};"::"r"(SCR+16384+f*64+((h^((f>>1)&3))<<4)),"r"(pack(z,1.f)),"r"(0u),"r"(0u),"r"(0u):"memory"); }
        fence_async_smem(); bar_sync(1,128);
        #pragma unroll
        for(int h=0;h<4;h++){
          float pq[2][16];
          const uint32_t wd=((SW+h*2048)>>4)|(1u<<16);
          wg_fence();
          #pragma unroll
          for(int mb=0;mb<2;mb++){
            wgmma_rs_n32z<1>(pq[mb],qf[mb][8*h],qf[mb][8*h+1],qf[mb][8*h+2],qf[mb][8*h+3],mk_desc2(wd,HI64));
            wgmma_rs_n32<1>(pq[mb],qf[mb][8*h+4],qf[mb][8*h+5],qf[mb][8*h+6],qf[mb][8*h+7],mk_desc2(wd+64,HI64),1); }
          wg_commit(); wg_wait<0>();
          const uint32_t kd=((SCR+h*4096)>>4)|(((16384+16*h-h*4096)>>4)<<16);
          #pragma unroll
          for(int mb=0;mb<2;mb++){
            float (&p)[16]=pq[mb]; fence_regs(p); float x0,x1,n0,n1; mnmx(p,x0,x1,n0,n1);
            x0*=-LOG2E; x1*=-LOG2E; n0*=LOG2E; n1*=LOG2E;
            uint32_t e[16];
            #pragma unroll
            for(int i=0;i<8;i++){ const bool hi=i&1;
              e[i]=pack(ex2(fmaf(p[2*i],LOG2E,hi?x1:x0)),ex2(fmaf(p[2*i+1],LOG2E,hi?x1:x0)));
              e[8+i]=pack(ex2(fmaf(p[2*i],-LOG2E,hi?n1:n0)),ex2(fmaf(p[2*i+1],-LOG2E,hi?n1:n0))); }
            float op[20], on[20];
            wg_fence();
            wgmma_rs_n40z<1>(op,e[0],e[1],e[2],e[3],mk_desc2(kd,HI64));
            wgmma_rs_n40<1>(op,e[4],e[5],e[6],e[7],mk_desc2(kd+64,HI64),1);
            wgmma_rs_n40z<1>(on,e[8],e[9],e[10],e[11],mk_desc2(kd+128,HI64));
            wgmma_rs_n40<1>(on,e[12],e[13],e[14],e[15],mk_desc2(kd+192,HI64),1);
            wg_commit(); wg_wait<0>(); fence_regs(op); fence_regs(on);
            const int r0=mb*64+wq*16+(lane>>2);
            float g0,g1; asm volatile("ld.shared.f32 %0, [%1];":"=f"(g0):"r"(SGATE+r0*4)); asm volatile("ld.shared.f32 %0, [%1];":"=f"(g1):"r"(SGATE+r0*4+32));
            float a0=rcp(op[17]), b0=rcp(on[17]), a1=rcp(op[19]), b1=rcp(on[19]);
            const float f0=g0/(op[16]*a0+on[16]*b0+1e-6f), f1=g1/(op[18]*a1+on[18]*b1+1e-6f);
            a0=__shfl_sync(0xffffffffu,a0*f0,lane&28); b0=__shfl_sync(0xffffffffu,b0*f0,lane&28);
            a1=__shfl_sync(0xffffffffu,a1*f1,lane&28); b1=__shfl_sync(0xffffffffu,b1*f1,lane&28);
            uint32_t* d=(uint32_t*)(g_o+(size_t)(m*128+r0)*2048+(4*hh+h)*32+(lane&3)*2);
            #pragma unroll
            for(int j=0;j<4;j++){ d[4*j]=pack(op[4*j]*a0+on[4*j]*b0,op[4*j+1]*a0+on[4*j+1]*b0); d[8192+4*j]=pack(op[4*j+2]*a1+on[4*j+2]*b1,op[4*j+3]*a1+on[4*j+3]*b1); }
          }
        }
        bar_sync(1,128);
        if(t128==0) flag_add(&g_cnt[C_OA+m]);
      } else {
        #pragma unroll
        for(int mb=0;mb<2;mb++){ const int row=mb*64+srow;
          #pragma unroll
          for(int c=0;c<8;c++){ const float* v=&acc[mb][8*c];
            stsm4(SCR+(c>>2)*16384+row*128+((((c&3)*2+(lane>>4))^(row&7))<<4), pack(v[0],v[1]),pack(v[2],v[3]),pack(v[4],v[5]),pack(v[6],v[7])); } }
        fence_async_smem(); bar_sync(1,128);
        if(t128==0){ tma2d_store(&mp.out,SCR,hh*128,m*128); tma2d_store(&mp.out,SCR+16384,hh*128+64,m*128); bulk_commit(); bulk_wait<0>(); }
      }
    }
  } else {
    reg_alloc<RA>();
    constexpr uint32_t kd0=(SKV>>4)|(1u<<16), vd0=((SKV+8192)>>4)|(((SONES-SKV-8192)>>4)<<16);
    uint32_t qd=((SQ+(warp>>2)*4096)>>4)|(1u<<16);
    float o[20], S0[32], S1[32], nb0=0, nb1=0; uint32_t P0[16], P1[16];
    #pragma unroll
    for(int i=0;i<20;i++) o[i]=0;
    #pragma unroll
    for(int i=0;i<16;i++) P1[i]=0;
    fence_regs(o);
    mbar_wait(B_Q,0);
    mbar_wait(B_KF,0);
    auto qk=[&](float (&S)[32], uint32_t q, uint32_t kd){
      wgmma_ss_n64z<0,0>(S,mk_desc2(q,HI64),mk_desc2(kd,HI64));
      wgmma_ss_n64<0,0>(S,mk_desc2(q+2,HI64),mk_desc2(kd+2,HI64),1); };
    wg_fence(); qk(S0,qd,kd0); wg_commit(); wg_wait<0>(); fence_regs(S0);
    auto epi=[&](int r){
      uint32_t cta,t; asm volatile("mov.u32 %0, %%ctaid.x;":"=r"(cta)); asm volatile("mov.u32 %0, %%tid.x;":"=r"(t));
      const int lr=(t>>5)*16+((t&31)>>2), head=8*r+(cta>>4);
      float g0,g1; asm volatile("ld.shared.f32 %0, [%1];":"=f"(g0):"r"(SGATE+lr*4)); asm volatile("ld.shared.f32 %0, [%1];":"=f"(g1):"r"(SGATE+lr*4+32));
      g0=__bfloat162float(__float2bfloat16(1.f-g0)); g1=__bfloat162float(__float2bfloat16(1.f-g1));
      const float f0=__fdividef(g0,o[16]), f1=__fdividef(g1,o[18]);
      bf16* orow=g_o+(size_t)((cta&15)*128+lr)*2048+1024+head*32;
      uint32_t* d=(uint32_t*)(orow+(t&3)*2);
      float t0=0,t1=0;
      #pragma unroll
      for(int j=0;j<4;j++){ d[4*j]=pack(o[4*j]*f0,o[4*j+1]*f0); d[8192+4*j]=pack(o[4*j+2]*f1,o[4*j+3]*f1);
        t0+=fabsf(o[4*j])+fabsf(o[4*j+1]); t1+=fabsf(o[4*j+2])+fabsf(o[4*j+3]); }
      const unsigned b0=__ballot_sync(0xffffffffu,!(o[16]<1e30f && t0<3e38f)), b1=__ballot_sync(0xffffffffu,!(o[18]<1e30f && t1<3e38f));
      if(b0|b1){
        const int ln=t&31; const uint8_t* kv=(const uint8_t*)(g_kvb+(size_t)head*16*8192);
        #pragma unroll 1
        for(int rr=0;rr<16;rr++){
          if(!(((rr<8?b0:b1)>>((rr&7)*4))&15)) continue;
          const int qrow=(t>>5)*16+rr; const uint32_t qa=SQ+r*8192+qrow*64;
          auto dot=[&](int key){ float s=0; const uint8_t* kr=kv+(key>>7)*16384+(key&127)*64;
            #pragma unroll 1
            for(int c=0;c<4;c++){ uint4 a=__ldcg((const uint4*)(kr+((c^((key>>1)&3))<<4))), b;
              asm volatile("ld.shared.v4.u32 {%0,%1,%2,%3}, [%4];":"=r"(b.x),"=r"(b.y),"=r"(b.z),"=r"(b.w):"r"(qa+((c^((qrow>>1)&3))<<4)));
              const uint32_t* pa=&a.x; const uint32_t* pb=&b.x;
              #pragma unroll
              for(int e=0;e<4;e++){ s=fmaf(__uint_as_float(pa[e]<<16),__uint_as_float(pb[e]<<16),s); s=fmaf(__uint_as_float(pa[e]&0xffff0000u),__uint_as_float(pb[e]&0xffff0000u),s); } }
            return s; };
          float mx=-INFINITY;
          #pragma unroll 1
          for(int k=ln;k<2048;k+=32) mx=fmaxf(mx,dot(k));
          #pragma unroll
          for(int of=16;of;of>>=1) mx=fmaxf(mx,__shfl_xor_sync(0xffffffffu,mx,of));
          float a=0,l=0;
          #pragma unroll 1
          for(int k0=0;k0<2048;k0+=32){ const float p=ex2((dot(k0+ln)-mx)*SC); l+=p;
            #pragma unroll 1
            for(int j=0;j<32;j++){ const int key=k0+j; const unsigned short vv=__ldcg((const unsigned short*)(kv+(key>>7)*16384+8192+(key&127)*64+(((ln>>3)^((key>>1)&3))<<4)+(ln&7)*2));
              a=fmaf(__shfl_sync(0xffffffffu,p,j),__uint_as_float((uint32_t)vv<<16),a); } }
          #pragma unroll
          for(int of=16;of;of>>=1) l+=__shfl_xor_sync(0xffffffffu,l,of);
          float g; asm volatile("ld.shared.f32 %0, [%1];":"=f"(g):"r"(SGATE+qrow*4));
          g=__bfloat162float(__float2bfloat16(1.f-g));
          __syncwarp();
          g_o[(size_t)((cta&15)*128+qrow)*2048+1024+head*32+ln]=__float2bfloat16(a*g/l);
        }
      }
      bar_arrive(2,288);
    };
    const bool l0 = lane==0;
    uint32_t zz; asm volatile("mov.u32 %0, 0;":"=r"(zz)); zz=__shfl_sync(0xffffffffu,zz,0);
    uint32_t sp=NST-1, sc=0, sn=1, phn=0;
    auto newmax=[&](float (&S)[32]){
      float m0=S[0],m1=S[2];
      #pragma unroll
      for(int i=0;i<8;i++){ m0=fmaxf(m0,fmaxf(S[4*i],S[4*i+1])); m1=fmaxf(m1,fmaxf(S[4*i+2],S[4*i+3])); }
      m0=fmaxf(m0,__shfl_xor_sync(0xffffffffu,m0,1)); m0=fmaxf(m0,__shfl_xor_sync(0xffffffffu,m0,2));
      m1=fmaxf(m1,__shfl_xor_sync(0xffffffffu,m1,1)); m1=fmaxf(m1,__shfl_xor_sync(0xffffffffu,m1,2));
      nb0=-(m0*SC+OFFS); nb1=-(m1*SC+OFFS); };
    newmax(S0);
    #pragma unroll
    for(int i=0;i<32;i++) S0[i]=fmaf(S0[i],SC,((i>>1)&1)?nb1:nb0);
    auto step=[&](const int r, const int MODE, const int U, float (&S)[32], uint32_t (&P)[16], float (&Sn)[32], uint32_t (&Pp)[16]){
      const bool first=(U==0)&&MODE==1, second=(U==1)&&MODE==1, last=(U==1)&&MODE==2;
      if(second && r>0) epi(r-1);
      if(last) qd+=512u;
      const uint32_t vd= U==0 ? vd0+sp*(1024u-(1024u<<16))+4*(64u-(64u<<16)) : vd0+sc*(1024u-(1024u<<16));
      const uint32_t kd= U==0 ? kd0+sc*1024u+256u : kd0+sn*1024u;
      bool ok=true;
      if(U==0 && !(MODE==2 && r==3)) ok=mbar_try(B_KF+8*sn, phn);
      wg_fence();
      qk(Sn,qd,kd);
      #pragma unroll
      for(int kk=0;kk<4;kk++){
        if(second&&kk==0) wgmma_rs_n40z<1>(o,Pp[4*kk],Pp[4*kk+1],Pp[4*kk+2],Pp[4*kk+3],mk_desc2(vd+kk*(64u-(64u<<16)),HI64));
        else wgmma_rs_n40<1>(o,Pp[4*kk],Pp[4*kk+1],Pp[4*kk+2],Pp[4*kk+3],mk_desc2(vd+kk*(64u-(64u<<16)),HI64),1); }
      wg_commit();
      #pragma unroll
      for(int i=0;i<PA;i++) P[i]=pack(ex2(S[2*i]),ex2(S[2*i+1]));
      #pragma unroll
      for(int i=0;i<PA;i++) asm volatile(""::"r"(P[i]));
      if(U==0){ if(__builtin_expect(!ok,0)) mbar_wait(B_KF+8*sn, phn); } else BOUND(1+MODE*8);
      #pragma unroll
      for(int i=PA;i<PART;i++) P[i]=pack(ex2(S[2*i]),ex2(S[2*i+1]));
      #pragma unroll
      for(int i=PA;i<PART;i++) asm volatile(""::"r"(P[i]));
      BOUND(2+U+MODE*8);
      wg_wait<0>(); fence_regs(Sn); fence_regs(o);
      if(last) newmax(Sn);
      #pragma unroll
      for(int i=PART;i<16;i++){
        #pragma unroll
        for(int j=(i-PART)*32/(16-PART);j<(i+1-PART)*32/(16-PART);j++) Sn[j]=fmaf(Sn[j],SC,((j>>1)&1)?nb1:nb0);
        P[i]=pack(ex2(S[2*i]),ex2(S[2*i+1])); }
      fence_regs(Sn);
      if(U==0){ if(l0 && !(first && r==0)) mbar_arrive(B_KE+8*sp); }
      else { sp=sc; sc=sn; sn=sn+1==NST?0:sn+1; phn^=(sn==0); }
    };
    #pragma unroll 1
    for(int r=0;r<4;r++){
      step(r,1,0,S0,P0,S1,P1); step(r,1,1,S1,P1,S0,P0);
      #pragma unroll 1
      for(int t=0;t<14;t++){ step(r,0,0,S0,P0,S1,P1); step(r,0,1,S1,P1,S0,P0); }
      step(r,2,0,S0,P0,S1,P1); step(r,2,1,S1,P1,S0,P0);
    }
    { const uint32_t vd=vd0+sp*(1024u-(1024u<<16))+4*(64u-(64u<<16));
      wg_fence();
      #pragma unroll
      for(int kk=0;kk<4;kk++) wgmma_rs_n40<1>(o,P1[4*kk],P1[4*kk+1],P1[4*kk+2],P1[4*kk+3],mk_desc2(vd+kk*(64u-(64u<<16)),HI64),1);
      wg_commit(); }
    wg_wait<0>(); fence_regs(o);
    epi(3);
  }
}

typedef CUresult (*PFN_enc)(CUtensorMap*, CUtensorMapDataType, cuuint32_t, void*, const cuuint64_t*, const cuuint64_t*, const cuuint32_t*, const cuuint32_t*, CUtensorMapInterleave, CUtensorMapSwizzle, CUtensorMapL2promotion, CUtensorMapFloatOOBfill);
static CUtensorMap mk_map(PFN_enc fn, const void* p, int rank, const cuuint64_t* dims, const cuuint64_t* strides, const cuuint32_t* box, CUtensorMapSwizzle sw){
  CUtensorMap m; cuuint32_t es[3]={1,1,1};
  fn(&m, CU_TENSOR_MAP_DATA_TYPE_BFLOAT16, rank, (void*)p, dims, strides, box, es, CU_TENSOR_MAP_INTERLEAVE_NONE, sw, CU_TENSOR_MAP_L2_PROMOTION_L2_256B, CU_TENSOR_MAP_FLOAT_OOB_FILL_NONE);
  return m; }
static CUtensorMap map2d(PFN_enc fn, const void* p, uint64_t inner, uint64_t outer, uint32_t bi, uint32_t bo, CUtensorMapSwizzle sw){
  cuuint64_t d[2]={inner,outer}, s[1]={inner*2}; cuuint32_t b[2]={bi,bo}; return mk_map(fn,p,2,d,s,b,sw); }

extern "C" void kernel_launch(void* const* d_in, const int* in_sizes, int n_in, void* d_out, int out_size){
  static bool init=false; static CUtensorMap mx, mw; static Maps mp; static const void* key[9];
  const void* cur[9]={d_in[0],d_in[1],d_in[2],d_in[3],d_in[5],d_in[6],d_in[7],d_out,nullptr};
  bool same=init; for(int i=0;i<8;i++) same = same && key[i]==cur[i];
  if(!same){
    PFN_enc fn=nullptr; cudaDriverEntryPointQueryResult q; cudaGetDriverEntryPoint("cuTensorMapEncodeTiled",(void**)&fn,cudaEnableDefault,&q);
    void* go; cudaGetSymbolAddress(&go,g_o);
    mx=map2d(fn,d_in[0],1024,2048,64,128,CU_TENSOR_MAP_SWIZZLE_128B);
    { cuuint64_t d[3]={1024,1024,3}, s[2]={6144,2048}; cuuint32_t b[3]={32,64,3}; mw=mk_map(fn,d_in[5],3,d,s,b,CU_TENSOR_MAP_SWIZZLE_64B); }
    mp.x=map2d(fn,d_in[0],1024,2048,32,128,CU_TENSOR_MAP_SWIZZLE_64B);
    mp.wa=map2d(fn,d_in[1],3072,1024,64,32,CU_TENSOR_MAP_SWIZZLE_128B);
    mp.go=map2d(fn,go,2048,2048,32,128,CU_TENSOR_MAP_SWIZZLE_64B);
    mp.woa=map2d(fn,d_in[3],1024,1024,64,32,CU_TENSOR_MAP_SWIZZLE_128B);
    mp.wob=map2d(fn,d_in[6],1024,1024,64,32,CU_TENSOR_MAP_SWIZZLE_128B);
    mp.out=map2d(fn,d_out,1024,2048,64,128,CU_TENSOR_MAP_SWIZZLE_128B);
    mp.wphi=map2d(fn,d_in[2],32,1024,32,128,CU_TENSOR_MAP_SWIZZLE_64B);
    cudaFuncSetAttribute(k_qkv,cudaFuncAttributeMaxDynamicSharedMemorySize,k1::SMEM);
    cudaFuncSetAttribute(k_main,cudaFuncAttributeMaxDynamicSharedMemorySize,k2::SMEM);
    for(int i=0;i<8;i++) key[i]=cur[i];
    init=true;
  }
  k_qkv<<<128,384,k1::SMEM,cudaStreamPerThread>>>(mx,mw,(const bf16*)d_in[0],(const bf16*)d_in[7]);
  cudaLaunchConfig_t cfg={}; cfg.gridDim=128; cfg.blockDim=512; cfg.dynamicSmemBytes=k2::SMEM; cfg.stream=cudaStreamPerThread;
  cudaLaunchAttribute at[1]; at[0].id=cudaLaunchAttributeProgrammaticStreamSerialization; at[0].val.programmaticStreamSerializationAllowed=1;
  cfg.attrs=at; cfg.numAttrs=1;
  cudaLaunchKernelEx(&cfg,k_main,mp);
}
```

```cpp
#include <cuda_runtime.h>
#include <cuda_bf16.h>
#include <cuda.h>
#include <stdint.h>

typedef __nv_bfloat16 bf16;
#define DEVI __device__ __forceinline__

DEVI uint32_t smem_u32(const void* p){ return (uint32_t)__cvta_generic_to_shared(p); }
DEVI void mbar_init(uint32_t bar, uint32_t cnt){ asm volatile("mbarrier.init.shared::cta.b64 [%0], %1;"::"r"(bar),"r"(cnt):"memory"); }
DEVI void mbar_expect_tx(uint32_t bar, uint32_t bytes){ asm volatile("mbarrier.arrive.expect_tx.shared::cta.b64 _, [%0], %1;"::"r"(bar),"r"(bytes):"memory"); }
DEVI void mbar_arrive(uint32_t bar){ asm volatile("mbarrier.arrive.shared::cta.b64 _, [%0];"::"r"(bar):"memory"); }
DEVI bool mbar_try(uint32_t bar, uint32_t parity){ uint32_t ok;
  asm volatile("{\n.reg .pred p;\nmbarrier.try_wait.parity.shared::cta.b64 p, [%1], %2;\nselp.u32 %0, 1, 0, p;\n}\n":"=r"(ok):"r"(bar),"r"(parity):"memory"); return ok; }
DEVI void mbar_wait(uint32_t bar, uint32_t parity){
  asm volatile("{\n.reg .pred p;\n.reg .u32 c;\nmov.u32 c, 0;\nLAB_WAIT:\nmbarrier.try_wait.parity.shared::cta.b64 p, [%0], %1;\n@p bra DONE;\nadd.u32 c, c, 1;\nsetp.lt.u32 p, c, 0x200000;\n@p bra LAB_WAIT;\ntrap;\nDONE:\n}\n"::"r"(bar),"r"(parity):"memory"); }
DEVI void tma2d(uint32_t dst, const CUtensorMap* m, int c0, int c1, uint32_t bar){
  asm volatile("cp.async.bulk.tensor.2d.shared::cluster.global.mbarrier::complete_tx::bytes [%0], [%1, {%3, %4}], [%2];"::"r"(dst),"l"(m),"r"(bar),"r"(c0),"r"(c1):"memory"); }
DEVI void tma2d_mc(uint32_t dst, const CUtensorMap* m, int c0, int c1, uint32_t bar, uint16_t mask){
  asm volatile("cp.async.bulk.tensor.2d.shared::cluster.global.mbarrier::complete_tx::bytes.multicast::cluster [%0], [%1, {%3, %4}], [%2], %5;"::"r"(dst),"l"(m),"r"(bar),"r"(c0),"r"(c1),"h"(mask):"memory"); }
DEVI void tma3d_mc(uint32_t dst, const CUtensorMap* m, int c0, int c1, int c2, uint32_t bar, uint16_t mask){
  asm volatile("cp.async.bulk.tensor.3d.shared::cluster.global.mbarrier::complete_tx::bytes.multicast::cluster [%0], [%1, {%3, %4, %5}], [%2], %6;"::"r"(dst),"l"(m),"r"(bar),"r"(c0),"r"(c1),"r"(c2),"h"(mask):"memory"); }
DEVI void tma4d_mc(uint32_t dst, const CUtensorMap* m, int c0, int c1, int c2, int c3, uint32_t bar, uint16_t mask){
  asm volatile("cp.async.bulk.tensor.4d.shared::cluster.global.mbarrier::complete_tx::bytes.multicast::cluster [%0], [%1, {%3, %4, %5, %6}], [%2], %7;"::"r"(dst),"l"(m),"r"(bar),"r"(c0),"r"(c1),"r"(c2),"r"(c3),"h"(mask):"memory"); }
DEVI void tma4d(uint32_t dst, const CUtensorMap* m, int c0, int c1, int c2, int c3, uint32_t bar){
  asm volatile("cp.async.bulk.tensor.4d.shared::cluster.global.mbarrier::complete_tx::bytes [%0], [%1, {%3, %4, %5, %6}], [%2];"::"r"(dst),"l"(m),"r"(bar),"r"(c0),"r"(c1),"r"(c2),"r"(c3):"memory"); }
DEVI uint32_t mapa(uint32_t a, uint32_t rank){ uint32_t r; asm("mapa.shared::cluster.u32 %0, %1, %2;":"=r"(r):"r"(a),"r"(rank)); return r; }
DEVI void mbar_arrive_cl(uint32_t a){ asm volatile("mbarrier.arrive.shared::cluster.b64 _, [%0];"::"r"(a):"memory"); }
DEVI void cluster_sync(){ asm volatile("barrier.cluster.arrive.release.aligned;\nbarrier.cluster.wait.acquire.aligned;":::"memory"); }
DEVI void tma3d(uint32_t dst, const CUtensorMap* m, int c0, int c1, int c2, uint32_t bar){
  asm volatile("cp.async.bulk.tensor.3d.shared::cluster.global.mbarrier::complete_tx::bytes [%0], [%1, {%3, %4, %5}], [%2];"::"r"(dst),"l"(m),"r"(bar),"r"(c0),"r"(c1),"r"(c2):"memory"); }
DEVI void tma2d_store(const CUtensorMap* m, uint32_t src, int c0, int c1){
  asm volatile("cp.async.bulk.tensor.2d.global.shared::cta.bulk_group [%0, {%2, %3}], [%1];"::"l"(m),"r"(src),"r"(c0),"r"(c1):"memory"); }
DEVI void bulk_g2s(uint32_t dst, const void* src, uint32_t bytes, uint32_t bar){
  asm volatile("cp.async.bulk.shared::cluster.global.mbarrier::complete_tx::bytes [%0], [%1], %2, [%3];"::"r"(dst),"l"(src),"r"(bytes),"r"(bar):"memory"); }
DEVI void bulk_s2g(void* dst, uint32_t src, uint32_t bytes){
  asm volatile("cp.async.bulk.global.shared::cta.bulk_group [%0], [%1], %2;"::"l"(dst),"r"(src),"r"(bytes):"memory"); }
DEVI void bulk_commit(){ asm volatile("cp.async.bulk.commit_group;":::"memory"); }
template<int N> DEVI void bulk_wait(){ asm volatile("cp.async.bulk.wait_group %0;"::"n"(N):"memory"); }
template<int N> DEVI void bulk_wait_read(){ asm volatile("cp.async.bulk.wait_group.read %0;"::"n"(N):"memory"); }
DEVI void fence_async_smem(){ asm volatile("fence.proxy.async.shared::cta;":::"memory"); }
DEVI void fence_async_all(){ asm volatile("fence.proxy.async.global;":::"memory"); }
DEVI void wg_fence(){ asm volatile("wgmma.fence.sync.aligned;":::"memory"); }
DEVI void wg_commit(){ asm volatile("wgmma.commit_group.sync.aligned;":::"memory"); }
template<int N> DEVI void wg_wait(){ asm volatile("wgmma.wait_group.sync.aligned %0;"::"n"(N):"memory"); }
DEVI uint64_t mk_desc2(uint32_t lo, uint32_t hi){ uint64_t d; asm("mov.b64 %0, {%1,%2};":"=l"(d):"r"(lo),"r"(hi)); return d; }
template<int R> DEVI void reg_alloc(){ asm volatile("setmaxnreg.inc.sync.aligned.u32 %0;"::"n"(R)); }
template<int R> DEVI void reg_dealloc(){ asm volatile("setmaxnreg.dec.sync.aligned.u32 %0;"::"n"(R)); }
template<int N> DEVI void fence_regs(float (&r)[N]){
  #pragma unroll
  for(int i=0;i<N;i++) asm volatile("":"+f"(r[i])::"memory"); }
DEVI void griddep_wait(){ asm volatile("griddepcontrol.wait;":::"memory"); }
DEVI void bar_sync(int id, int n){ asm volatile("bar.sync %0, %1;"::"r"(id),"r"(n):"memory"); }
DEVI void bar_arrive(int id, int n){ asm volatile("bar.arrive %0, %1;"::"r"(id),"r"(n):"memory"); }
DEVI float ex2(float x){ float y; asm("ex2.approx.ftz.f32 %0,%1;":"=f"(y):"f"(x)); return y; }
DEVI float rcp(float x){ float y; asm("rcp.approx.ftz.f32 %0,%1;":"=f"(y):"f"(x)); return y; }
DEVI uint32_t pack(float lo,float hi){ uint32_t y; asm("cvt.rn.bf16x2.f32 %0,%1,%2;":"=r"(y):"f"(hi),"f"(lo)); return y; }
DEVI void stsm4(uint32_t a, uint32_t r0, uint32_t r1, uint32_t r2, uint32_t r3){
  asm volatile("stmatrix.sync.aligned.m8n8.x4.shared.b16 [%0], {%1,%2,%3,%4};"::"r"(a),"r"(r0),"r"(r1),"r"(r2),"r"(r3):"memory"); }
DEVI void flag_add(unsigned* p){ asm volatile("fence.acq_rel.gpu;\nred.relaxed.gpu.global.add.u32 [%0], 1;"::"l"(p):"memory"); }
DEVI unsigned ld_acq(const unsigned* p){ unsigned v; asm volatile("ld.acquire.gpu.global.u32 %0, [%1];":"=r"(v):"l"(p):"memory"); return v; }
DEVI void flag_set(unsigned* p, unsigned v){ asm volatile("st.release.gpu.global.u32 [%0], %1;"::"l"(p),"r"(v):"memory"); }
DEVI void flag_set_rlx(unsigned* p, unsigned v){ asm volatile("fence.proxy.async.global;\nst.relaxed.gpu.global.u32 [%0], %1;"::"l"(p),"r"(v):"memory"); }
DEVI void flag_add_rlx(unsigned* p){ asm volatile("fence.proxy.async.global;\nred.relaxed.gpu.global.add.u32 [%0], 1;"::"l"(p):"memory"); }
DEVI void flag_wait(const unsigned* p, unsigned target){
  for(int i=0;i<(1<<22);i++){ if((int)(ld_acq(p)-target)>=0) return; __nanosleep(40); }
  asm volatile("trap;"); }
DEVI void flag_wait_eq(const unsigned* p, unsigned tag){
  for(int i=0;i<(1<<22);i++){ if(ld_acq(p)==tag) return; __nanosleep(40); }
  asm volatile("trap;"); }
DEVI void red2(float* p, float a, float b){ asm volatile("red.relaxed.gpu.global.add.v2.f32 [%0], {%1,%2};"::"l"(p),"f"(a),"f"(b):"memory"); }
DEVI void red1(float* p, float a){ asm volatile("red.relaxed.gpu.global.add.f32 [%0], %1;"::"l"(p),"f"(a):"memory"); }
#define BOUND(c) asm volatile("{\n.reg .pred p;\nsetp.eq.u32 p, %0, %1;\n@p exit;\n}\n"::"r"(zz),"r"(c):"memory")
template<int TA, int TB> DEVI void wgmma_ss_n192(float (&d)[96], uint64_t da, uint64_t db, int sd){
  asm volatile("{\n.reg .pred p;\nsetp.ne.b32 p, %98, 0;\n"
    "wgmma.mma_async.sync.aligned.m64n192k16.f32.bf16.bf16 {%0, %1, %2, %3, %4, %5, %6, %7, %8, %9, %10, %11, %12, %13, %14, %15, %16, %17, %18, %19, %20, %21, %22, %23, %24, %25, %26, %27, %28, %29, %30, %31, %32, %33, %34, %35, %36, %37, %38, %39, %40, %41, %42, %43, %44, %45, %46, %47, %48, %49, %50, %51, %52, %53, %54, %55, %56, %57, %58, %59, %60, %61, %62, %63, %64, %65, %66, %67, %68, %69, %70, %71, %72, %73, %74, %75, %76, %77, %78, %79, %80, %81, %82, %83, %84, %85, %86, %87, %88, %89, %90, %91, %92, %93, %94, %95}, %96, %97, p, 1, 1, %99, %100;\n}\n"
    : "+f"(d[0]), "+f"(d[1]), "+f"(d[2]), "+f"(d[3]), "+f"(d[4]), "+f"(d[5]), "+f"(d[6]), "+f"(d[7]), "+f"(d[8]), "+f"(d[9]), "+f"(d[10]), "+f"(d[11]), "+f"(d[12]), "+f"(d[13]), "+f"(d[14]), "+f"(d[15]), "+f"(d[16]), "+f"(d[17]), "+f"(d[18]), "+f"(d[19]), "+f"(d[20]), "+f"(d[21]), "+f"(d[22]), "+f"(d[23]), "+f"(d[24]), "+f"(d[25]), "+f"(d[26]), "+f"(d[27]), "+f"(d[28]), "+f"(d[29]), "+f"(d[30]), "+f"(d[31]), "+f"(d[32]), "+f"(d[33]), "+f"(d[34]), "+f"(d[35]), "+f"(d[36]), "+f"(d[37]), "+f"(d[38]), "+f"(d[39]), "+f"(d[40]), "+f"(d[41]), "+f"(d[42]), "+f"(d[43]), "+f"(d[44]), "+f"(d[45]), "+f"(d[46]), "+f"(d[47]), "+f"(d[48]), "+f"(d[49]), "+f"(d[50]), "+f"(d[51]), "+f"(d[52]), "+f"(d[53]), "+f"(d[54]), "+f"(d[55]), "+f"(d[56]), "+f"(d[57]), "+f"(d[58]), "+f"(d[59]), "+f"(d[60]), "+f"(d[61]), "+f"(d[62]), "+f"(d[63]), "+f"(d[64]), "+f"(d[65]), "+f"(d[66]), "+f"(d[67]), "+f"(d[68]), "+f"(d[69]), "+f"(d[70]), "+f"(d[71]), "+f"(d[72]), "+f"(d[73]), "+f"(d[74]), "+f"(d[75]), "+f"(d[76]), "+f"(d[77]), "+f"(d[78]), "+f"(d[79]), "+f"(d[80]), "+f"(d[81]), "+f"(d[82]), "+f"(d[83]), "+f"(d[84]), "+f"(d[85]), "+f"(d[86]), "+f"(d[87]), "+f"(d[88]), "+f"(d[89]), "+f"(d[90]), "+f"(d[91]), "+f"(d[92]), "+f"(d[93]), "+f"(d[94]), "+f"(d[95])
    : "l"(da), "l"(db), "r"(sd), "n"(TA), "n"(TB));
}
template<int TA, int TB> DEVI void wgmma_ss_n192z(float (&d)[96], uint64_t da, uint64_t db){
  asm volatile("{\n.reg .pred p;\nsetp.ne.b32 p, 0, 0;\n"
    "wgmma.mma_async.sync.aligned.m64n192k16.f32.bf16.bf16 {%0, %1, %2, %3, %4, %5, %6, %7, %8, %9, %10, %11, %12, %13, %14, %15, %16, %17, %18, %19, %20, %21, %22, %23, %24, %25, %26, %27, %28, %29, %30, %31, %32, %33, %34, %35, %36, %37, %38, %39, %40, %41, %42, %43, %44, %45, %46, %47, %48, %49, %50, %51, %52, %53, %54, %55, %56, %57, %58, %59, %60, %61, %62, %63, %64, %65, %66, %67, %68, %69, %70, %71, %72, %73, %74, %75, %76, %77, %78, %79, %80, %81, %82, %83, %84, %85, %86, %87, %88, %89, %90, %91, %92, %93, %94, %95}, %96, %97, p, 1, 1, %98, %99;\n}\n"
    : "=f"(d[0]), "=f"(d[1]), "=f"(d[2]), "=f"(d[3]), "=f"(d[4]), "=f"(d[5]), "=f"(d[6]), "=f"(d[7]), "=f"(d[8]), "=f"(d[9]), "=f"(d[10]), "=f"(d[11]), "=f"(d[12]), "=f"(d[13]), "=f"(d[14]), "=f"(d[15]), "=f"(d[16]), "=f"(d[17]), "=f"(d[18]), "=f"(d[19]), "=f"(d[20]), "=f"(d[21]), "=f"(d[22]), "=f"(d[23]), "=f"(d[24]), "=f"(d[25]), "=f"(d[26]), "=f"(d[27]), "=f"(d[28]), "=f"(d[29]), "=f"(d[30]), "=f"(d[31]), "=f"(d[32]), "=f"(d[33]), "=f"(d[34]), "=f"(d[35]), "=f"(d[36]), "=f"(d[37]), "=f"(d[38]), "=f"(d[39]), "=f"(d[40]), "=f"(d[41]), "=f"(d[42]), "=f"(d[43]), "=f"(d[44]), "=f"(d[45]), "=f"(d[46]), "=f"(d[47]), "=f"(d[48]), "=f"(d[49]), "=f"(d[50]), "=f"(d[51]), "=f"(d[52]), "=f"(d[53]), "=f"(d[54]), "=f"(d[55]), "=f"(d[56]), "=f"(d[57]), "=f"(d[58]), "=f"(d[59]), "=f"(d[60]), "=f"(d[61]), "=f"(d[62]), "=f"(d[63]), "=f"(d[64]), "=f"(d[65]), "=f"(d[66]), "=f"(d[67]), "=f"(d[68]), "=f"(d[69]), "=f"(d[70]), "=f"(d[71]), "=f"(d[72]), "=f"(d[73]), "=f"(d[74]), "=f"(d[75]), "=f"(d[76]), "=f"(d[77]), "=f"(d[78]), "=f"(d[79]), "=f"(d[80]), "=f"(d[81]), "=f"(d[82]), "=f"(d[83]), "=f"(d[84]), "=f"(d[85]), "=f"(d[86]), "=f"(d[87]), "=f"(d[88]), "=f"(d[89]), "=f"(d[90]), "=f"(d[91]), "=f"(d[92]), "=f"(d[93]), "=f"(d[94]), "=f"(d[95])
    : "l"(da), "l"(db), "n"(TA), "n"(TB));
}
template<int TA, int TB> DEVI void wgmma_ss_n128(float (&d)[64], uint64_t da, uint64_t db, int sd){
  asm volatile("{\n.reg .pred p;\nsetp.ne.b32 p, %66, 0;\n"
    "wgmma.mma_async.sync.aligned.m64n128k16.f32.bf16.bf16 {%0, %1, %2, %3, %4, %5, %6, %7, %8, %9, %10, %11, %12, %13, %14, %15, %16, %17, %18, %19, %20, %21, %22, %23, %24, %25, %26, %27, %28, %29, %30, %31, %32, %33, %34, %35, %36, %37, %38, %39, %40, %41, %42, %43, %44, %45, %46, %47, %48, %49, %50, %51, %52, %53, %54, %55, %56, %57, %58, %59, %60, %61, %62, %63}, %64, %65, p, 1, 1, %67, %68;\n}\n"
    : "+f"(d[0]), "+f"(d[1]), "+f"(d[2]), "+f"(d[3]), "+f"(d[4]), "+f"(d[5]), "+f"(d[6]), "+f"(d[7]), "+f"(d[8]), "+f"(d[9]), "+f"(d[10]), "+f"(d[11]), "+f"(d[12]), "+f"(d[13]), "+f"(d[14]), "+f"(d[15]), "+f"(d[16]), "+f"(d[17]), "+f"(d[18]), "+f"(d[19]), "+f"(d[20]), "+f"(d[21]), "+f"(d[22]), "+f"(d[23]), "+f"(d[24]), "+f"(d[25]), "+f"(d[26]), "+f"(d[27]), "+f"(d[28]), "+f"(d[29]), "+f"(d[30]), "+f"(d[31]), "+f"(d[32]), "+f"(d[33]), "+f"(d[34]), "+f"(d[35]), "+f"(d[36]), "+f"(d[37]), "+f"(d[38]), "+f"(d[39]), "+f"(d[40]), "+f"(d[41]), "+f"(d[42]), "+f"(d[43]), "+f"(d[44]), "+f"(d[45]), "+f"(d[46]), "+f"(d[47]), "+f"(d[48]), "+f"(d[49]), "+f"(d[50]), "+f"(d[51]), "+f"(d[52]), "+f"(d[53]), "+f"(d[54]), "+f"(d[55]), "+f"(d[56]), "+f"(d[57]), "+f"(d[58]), "+f"(d[59]), "+f"(d[60]), "+f"(d[61]), "+f"(d[62]), "+f"(d[63])
    : "l"(da), "l"(db), "r"(sd), "n"(TA), "n"(TB));
}
template<int TA, int TB> DEVI void wgmma_ss_n128z(float (&d)[64], uint64_t da, uint64_t db){
  asm volatile("{\n.reg .pred p;\nsetp.ne.b32 p, 0, 0;\n"
    "wgmma.mma_async.sync.aligned.m64n128k16.f32.bf16.bf16 {%0, %1, %2, %3, %4, %5, %6, %7, %8, %9, %10, %11, %12, %13, %14, %15, %16, %17, %18, %19, %20, %21, %22, %23, %24, %25, %26, %27, %28, %29, %30, %31, %32, %33, %34, %35, %36, %37, %38, %39, %40, %41, %42, %43, %44, %45, %46, %47, %48, %49, %50, %51, %52, %53, %54, %55, %56, %57, %58, %59, %60, %61, %62, %63}, %64, %65, p, 1, 1, %66, %67;\n}\n"
    : "=f"(d[0]), "=f"(d[1]), "=f"(d[2]), "=f"(d[3]), "=f"(d[4]), "=f"(d[5]), "=f"(d[6]), "=f"(d[7]), "=f"(d[8]), "=f"(d[9]), "=f"(d[10]), "=f"(d[11]), "=f"(d[12]), "=f"(d[13]), "=f"(d[14]), "=f"(d[15]), "=f"(d[16]), "=f"(d[17]), "=f"(d[18]), "=f"(d[19]), "=f"(d[20]), "=f"(d[21]), "=f"(d[22]), "=f"(d[23]), "=f"(d[24]), "=f"(d[25]), "=f"(d[26]), "=f"(d[27]), "=f"(d[28]), "=f"(d[29]), "=f"(d[30]), "=f"(d[31]), "=f"(d[32]), "=f"(d[33]), "=f"(d[34]), "=f"(d[35]), "=f"(d[36]), "=f"(d[37]), "=f"(d[38]), "=f"(d[39]), "=f"(d[40]), "=f"(d[41]), "=f"(d[42]), "=f"(d[43]), "=f"(d[44]), "=f"(d[45]), "=f"(d[46]), "=f"(d[47]), "=f"(d[48]), "=f"(d[49]), "=f"(d[50]), "=f"(d[51]), "=f"(d[52]), "=f"(d[53]), "=f"(d[54]), "=f"(d[55]), "=f"(d[56]), "=f"(d[57]), "=f"(d[58]), "=f"(d[59]), "=f"(d[60]), "=f"(d[61]), "=f"(d[62]), "=f"(d[63])
    : "l"(da), "l"(db), "n"(TA), "n"(TB));
}
template<int TA, int TB> DEVI void wgmma_ss_n64(float (&d)[32], uint64_t da, uint64_t db, int sd){
  asm volatile("{\n.reg .pred p;\nsetp.ne.b32 p, %34, 0;\n"
    "wgmma.mma_async.sync.aligned.m64n64k16.f32.bf16.bf16 {%0, %1, %2, %3, %4, %5, %6, %7, %8, %9, %10, %11, %12, %13, %14, %15, %16, %17, %18, %19, %20, %21, %22, %23, %24, %25, %26, %27, %28, %29, %30, %31}, %32, %33, p, 1, 1, %35, %36;\n}\n"
    : "+f"(d[0]), "+f"(d[1]), "+f"(d[2]), "+f"(d[3]), "+f"(d[4]), "+f"(d[5]), "+f"(d[6]), "+f"(d[7]), "+f"(d[8]), "+f"(d[9]), "+f"(d[10]), "+f"(d[11]), "+f"(d[12]), "+f"(d[13]), "+f"(d[14]), "+f"(d[15]), "+f"(d[16]), "+f"(d[17]), "+f"(d[18]), "+f"(d[19]), "+f"(d[20]), "+f"(d[21]), "+f"(d[22]), "+f"(d[23]), "+f"(d[24]), "+f"(d[25]), "+f"(d[26]), "+f"(d[27]), "+f"(d[28]), "+f"(d[29]), "+f"(d[30]), "+f"(d[31])
    : "l"(da), "l"(db), "r"(sd), "n"(TA), "n"(TB));
}
template<int TA, int TB> DEVI void wgmma_ss_n64z(float (&d)[32], uint64_t da, uint64_t db){
  asm volatile("{\n.reg .pred p;\nsetp.ne.b32 p, 0, 0;\n"
    "wgmma.mma_async.sync.aligned.m64n64k16.f32.bf16.bf16 {%0, %1, %2, %3, %4, %5, %6, %7, %8, %9, %10, %11, %12, %13, %14, %15, %16, %17, %18, %19, %20, %21, %22, %23, %24, %25, %26, %27, %28, %29, %30, %31}, %32, %33, p, 1, 1, %34, %35;\n}\n"
    : "=f"(d[0]), "=f"(d[1]), "=f"(d[2]), "=f"(d[3]), "=f"(d[4]), "=f"(d[5]), "=f"(d[6]), "=f"(d[7]), "=f"(d[8]), "=f"(d[9]), "=f"(d[10]), "=f"(d[11]), "=f"(d[12]), "=f"(d[13]), "=f"(d[14]), "=f"(d[15]), "=f"(d[16]), "=f"(d[17]), "=f"(d[18]), "=f"(d[19]), "=f"(d[20]), "=f"(d[21]), "=f"(d[22]), "=f"(d[23]), "=f"(d[24]), "=f"(d[25]), "=f"(d[26]), "=f"(d[27]), "=f"(d[28]), "=f"(d[29]), "=f"(d[30]), "=f"(d[31])
    : "l"(da), "l"(db), "n"(TA), "n"(TB));
}
template<int TB> DEVI void wgmma_rs_n40(float (&d)[20], uint32_t a0, uint32_t a1, uint32_t a2, uint32_t a3, uint64_t db, int sd){
  asm volatile("{\n.reg .pred p;\nsetp.ne.b32 p, %25, 0;\n"
    "wgmma.mma_async.sync.aligned.m64n40k16.f32.bf16.bf16 {%0, %1, %2, %3, %4, %5, %6, %7, %8, %9, %10, %11, %12, %13, %14, %15, %16, %17, %18, %19}, {%20,%21,%22,%23}, %24, p, 1, 1, %26;\n}\n"
    : "+f"(d[0]), "+f"(d[1]), "+f"(d[2]), "+f"(d[3]), "+f"(d[4]), "+f"(d[5]), "+f"(d[6]), "+f"(d[7]), "+f"(d[8]), "+f"(d[9]), "+f"(d[10]), "+f"(d[11]), "+f"(d[12]), "+f"(d[13]), "+f"(d[14]), "+f"(d[15]), "+f"(d[16]), "+f"(d[17]), "+f"(d[18]), "+f"(d[19])
    : "r"(a0), "r"(a1), "r"(a2), "r"(a3), "l"(db), "r"(sd), "n"(TB));
}
template<int TB> DEVI void wgmma_rs_n40z(float (&d)[20], uint32_t a0, uint32_t a1, uint32_t a2, uint32_t a3, uint64_t db){
  asm volatile("{\n.reg .pred p;\nsetp.ne.b32 p, 0, 0;\n"
    "wgmma.mma_async.sync.aligned.m64n40k16.f32.bf16.bf16 {%0, %1, %2, %3, %4, %5, %6, %7, %8, %9, %10, %11, %12, %13, %14, %15, %16, %17, %18, %19}, {%20,%21,%22,%23}, %24, p, 1, 1, %25;\n}\n"
    : "=f"(d[0]), "=f"(d[1]), "=f"(d[2]), "=f"(d[3]), "=f"(d[4]), "=f"(d[5]), "=f"(d[6]), "=f"(d[7]), "=f"(d[8]), "=f"(d[9]), "=f"(d[10]), "=f"(d[11]), "=f"(d[12]), "=f"(d[13]), "=f"(d[14]), "=f"(d[15]), "=f"(d[16]), "=f"(d[17]), "=f"(d[18]), "=f"(d[19])
    : "r"(a0), "r"(a1), "r"(a2), "r"(a3), "l"(db), "n"(TB));
}
template<int TA, int TB> DEVI void wgmma_ss_n40(float (&d)[20], uint64_t da, uint64_t db, int sd){
  asm volatile("{\n.reg .pred p;\nsetp.ne.b32 p, %22, 0;\n"
    "wgmma.mma_async.sync.aligned.m64n40k16.f32.bf16.bf16 {%0, %1, %2, %3, %4, %5, %6, %7, %8, %9, %10, %11, %12, %13, %14, %15, %16, %17, %18, %19}, %20, %21, p, 1, 1, %23, %24;\n}\n"
    : "+f"(d[0]), "+f"(d[1]), "+f"(d[2]), "+f"(d[3]), "+f"(d[4]), "+f"(d[5]), "+f"(d[6]), "+f"(d[7]), "+f"(d[8]), "+f"(d[9]), "+f"(d[10]), "+f"(d[11]), "+f"(d[12]), "+f"(d[13]), "+f"(d[14]), "+f"(d[15]), "+f"(d[16]), "+f"(d[17]), "+f"(d[18]), "+f"(d[19])
    : "l"(da), "l"(db), "r"(sd), "n"(TA), "n"(TB));
}
template<int TA, int TB> DEVI void wgmma_ss_n40z(float (&d)[20], uint64_t da, uint64_t db){
  asm volatile("{\n.reg .pred p;\nsetp.ne.b32 p, 0, 0;\n"
    "wgmma.mma_async.sync.aligned.m64n40k16.f32.bf16.bf16 {%0, %1, %2, %3, %4, %5, %6, %7, %8, %9, %10, %11, %12, %13, %14, %15, %16, %17, %18, %19}, %20, %21, p, 1, 1, %22, %23;\n}\n"
    : "=f"(d[0]), "=f"(d[1]), "=f"(d[2]), "=f"(d[3]), "=f"(d[4]), "=f"(d[5]), "=f"(d[6]), "=f"(d[7]), "=f"(d[8]), "=f"(d[9]), "=f"(d[10]), "=f"(d[11]), "=f"(d[12]), "=f"(d[13]), "=f"(d[14]), "=f"(d[15]), "=f"(d[16]), "=f"(d[17]), "=f"(d[18]), "=f"(d[19])
    : "l"(da), "l"(db), "n"(TA), "n"(TB));
}
template<int TB> DEVI void wgmma_rs_n32(float (&d)[16], uint32_t a0, uint32_t a1, uint32_t a2, uint32_t a3, uint64_t db, int sd){
  asm volatile("{\n.reg .pred p;\nsetp.ne.b32 p, %21, 0;\n"
    "wgmma.mma_async.sync.aligned.m64n32k16.f32.bf16.bf16 {%0, %1, %2, %3, %4, %5, %6, %7, %8, %9, %10, %11, %12, %13, %14, %15}, {%16,%17,%18,%19}, %20, p, 1, 1, %22;\n}\n"
    : "+f"(d[0]), "+f"(d[1]), "+f"(d[2]), "+f"(d[3]), "+f"(d[4]), "+f"(d[5]), "+f"(d[6]), "+f"(d[7]), "+f"(d[8]), "+f"(d[9]), "+f"(d[10]), "+f"(d[11]), "+f"(d[12]), "+f"(d[13]), "+f"(d[14]), "+f"(d[15])
    : "r"(a0), "r"(a1), "r"(a2), "r"(a3), "l"(db), "r"(sd), "n"(TB));
}
template<int TB> DEVI void wgmma_rs_n32z(float (&d)[16], uint32_t a0, uint32_t a1, uint32_t a2, uint32_t a3, uint64_t db){
  asm volatile("{\n.reg .pred p;\nsetp.ne.b32 p, 0, 0;\n"
    "wgmma.mma_async.sync.aligned.m64n32k16.f32.bf16.bf16 {%0, %1, %2, %3, %4, %5, %6, %7, %8, %9, %10, %11, %12, %13, %14, %15}, {%16,%17,%18,%19}, %20, p, 1, 1, %21;\n}\n"
    : "=f"(d[0]), "=f"(d[1]), "=f"(d[2]), "=f"(d[3]), "=f"(d[4]), "=f"(d[5]), "=f"(d[6]), "=f"(d[7]), "=f"(d[8]), "=f"(d[9]), "=f"(d[10]), "=f"(d[11]), "=f"(d[12]), "=f"(d[13]), "=f"(d[14]), "=f"(d[15])
    : "r"(a0), "r"(a1), "r"(a2), "r"(a3), "l"(db), "n"(TB));
}
template<int TB> DEVI void wgmma_rs_n64(float (&d)[32], uint32_t a0, uint32_t a1, uint32_t a2, uint32_t a3, uint64_t db, int sd){
  asm volatile("{\n.reg .pred p;\nsetp.ne.b32 p, %37, 0;\n"
    "wgmma.mma_async.sync.aligned.m64n64k16.f32.bf16.bf16 {%0, %1, %2, %3, %4, %5, %6, %7, %8, %9, %10, %11, %12, %13, %14, %15, %16, %17, %18, %19, %20, %21, %22, %23, %24, %25, %26, %27, %28, %29, %30, %31}, {%32,%33,%34,%35}, %36, p, 1, 1, %38;\n}\n"
    : "+f"(d[0]), "+f"(d[1]), "+f"(d[2]), "+f"(d[3]), "+f"(d[4]), "+f"(d[5]), "+f"(d[6]), "+f"(d[7]), "+f"(d[8]), "+f"(d[9]), "+f"(d[10]), "+f"(d[11]), "+f"(d[12]), "+f"(d[13]), "+f"(d[14]), "+f"(d[15]), "+f"(d[16]), "+f"(d[17]), "+f"(d[18]), "+f"(d[19]), "+f"(d[20]), "+f"(d[21]), "+f"(d[22]), "+f"(d[23]), "+f"(d[24]), "+f"(d[25]), "+f"(d[26]), "+f"(d[27]), "+f"(d[28]), "+f"(d[29]), "+f"(d[30]), "+f"(d[31])
    : "r"(a0), "r"(a1), "r"(a2), "r"(a3), "l"(db), "r"(sd), "n"(TB));
}
template<int TB> DEVI void wgmma_rs_n64z(float (&d)[32], uint32_t a0, uint32_t a1, uint32_t a2, uint32_t a3, uint64_t db){
  asm volatile("{\n.reg .pred p;\nsetp.ne.b32 p, 0, 0;\n"
    "wgmma.mma_async.sync.aligned.m64n64k16.f32.bf16.bf16 {%0, %1, %2, %3, %4, %5, %6, %7, %8, %9, %10, %11, %12, %13, %14, %15, %16, %17, %18, %19, %20, %21, %22, %23, %24, %25, %26, %27, %28, %29, %30, %31}, {%32,%33,%34,%35}, %36, p, 1, 1, %37;\n}\n"
    : "=f"(d[0]), "=f"(d[1]), "=f"(d[2]), "=f"(d[3]), "=f"(d[4]), "=f"(d[5]), "=f"(d[6]), "=f"(d[7]), "=f"(d[8]), "=f"(d[9]), "=f"(d[10]), "=f"(d[11]), "=f"(d[12]), "=f"(d[13]), "=f"(d[14]), "=f"(d[15]), "=f"(d[16]), "=f"(d[17]), "=f"(d[18]), "=f"(d[19]), "=f"(d[20]), "=f"(d[21]), "=f"(d[22]), "=f"(d[23]), "=f"(d[24]), "=f"(d[25]), "=f"(d[26]), "=f"(d[27]), "=f"(d[28]), "=f"(d[29]), "=f"(d[30]), "=f"(d[31])
    : "r"(a0), "r"(a1), "r"(a2), "r"(a3), "l"(db), "n"(TB));
}

__device__ __align__(1024) bf16 g_q[32*2048*32];
__device__ __align__(1024) bf16 g_kvb[32*16*2*128*32];
__device__ __align__(1024) bf16 g_o[2048*2048];
__device__ __align__(16) float g_kv[2*32*64*40];
__device__ __align__(1024) uint4 g_kvi[8*1280];
__device__ __align__(16) unsigned g_cnt[192];
__device__ unsigned g_tile[32*16];
__device__ unsigned g_epoch;
__device__ float g_gate[2048];
#define TS(i)
#define TC(i)
constexpr int C_KV=0, C_KI=8, C_OA=16, C_OB=32, C_G=96, C_OP=128;

constexpr float LOG2E = 1.4426950408889634f;
constexpr float SC = 0.17677669529663687f*LOG2E;
constexpr float OFFS = 88.f;
constexpr uint32_t HI64 = (512u>>4)|(2u<<30);
constexpr uint32_t HI128 = (1024u>>4)|(1u<<30);
constexpr uint32_t SB = 1024;

#define RAV 144
#define RGV 192
#define PAV 3
#define PARTV 10
#define GCG 1
#define GW 1
namespace k2 {
  constexpr int NST=4, GST=4;
  constexpr uint32_t SQ=SB, SKV=SQ+16384, SG=SKV+NST*16384, SW=SG+GST*32768, SONES=SW+8192, SGATE=SONES+1024, BARS=SGATE+512;
  constexpr uint32_t B_KF=BARS, B_KE=BARS+32, B_Q=BARS+64, B_W=BARS+80, B_GF=BARS+128, B_GE=BARS+192, B_PF=BARS+256, B_PE=BARS+320, B_E=BARS+96, SEP=BARS+384;
  constexpr uint32_t PST=40960, PR=SKV+32768;
  constexpr uint32_t SMEM=BARS+512-SB;
  constexpr int RA=RAV, RG=RGV, RP=512-2*RAV-RGV;
  constexpr int PA=PAV, PART=PARTV;
}
struct Maps { CUtensorMap x, wa, go, woa, wob, out, wphi, wb3, wb2, wb; const bf16 *xp, *gw; };

DEVI void mnmx(const float (&p)[16], float& x0, float& x1, float& n0, float& n1){
  x0=fmaxf(p[0],p[1]); n0=fminf(p[0],p[1]); x1=fmaxf(p[2],p[3]); n1=fminf(p[2],p[3]);
  #pragma unroll
  for(int j=1;j<4;j++){ x0=fmaxf(x0,fmaxf(p[4*j],p[4*j+1])); n0=fminf(n0,fminf(p[4*j],p[4*j+1])); x1=fmaxf(x1,fmaxf(p[4*j+2],p[4*j+3])); n1=fminf(n1,fminf(p[4*j+2],p[4*j+3])); }
  #pragma unroll
  for(int o=1;o<4;o<<=1){ x0=fmaxf(x0,__shfl_xor_sync(0xffffffffu,x0,o)); x1=fmaxf(x1,__shfl_xor_sync(0xffffffffu,x1,o));
                          n0=fminf(n0,__shfl_xor_sync(0xffffffffu,n0,o)); n1=fminf(n1,__shfl_xor_sync(0xffffffffu,n1,o)); }
}

__global__ void __launch_bounds__(512,1) k_main(const __grid_constant__ Maps mp){
  using namespace k2;
  extern __shared__ __align__(1024) uint8_t smem_raw[];
  const uint32_t cb=smem_u32(smem_raw)-SB;
  if(cb&0xffffffu) asm volatile("trap;");
  const uint32_t B_KF=cb+k2::B_KF, B_KE=cb+k2::B_KE, B_Q=cb+k2::B_Q, B_W=cb+k2::B_W, B_GF=cb+k2::B_GF, B_GE=cb+k2::B_GE, SGATE=cb+k2::SGATE,
                 B_PF=cb+k2::B_PF, B_PE=cb+k2::B_PE, B_E=cb+k2::B_E, SEP=cb+k2::SEP;
  const int tid=threadIdx.x, lane=tid&31, warp=__shfl_sync(0xffffffffu,tid>>5,0);
  const int m=blockIdx.x&15, hh=blockIdx.x>>4;
  if(tid==0){
    for(int s=0;s<NST;s++){ mbar_init(B_KF+8*s,1); mbar_init(B_KE+8*s,8); }
    for(int s=0;s<GST;s++){ mbar_init(B_GF+8*s,1); mbar_init(B_GE+8*s,8); }
    mbar_init(B_E,1);
    mbar_init(B_Q,1); mbar_init(B_Q+8,1); mbar_init(B_W,1); mbar_init(B_W+8,1);
    asm volatile("fence.mbarrier_init.release.cluster;":::"memory"); }
  if(tid==416){
    for(int s=0;s<4;s++){ mbar_init(B_PF+8*s,1); mbar_init(B_PE+8*s,16); }
    asm volatile("fence.mbarrier_init.release.cluster;":::"memory"); fence_async_smem();
    for(int s=0;s<4;s++){ mbar_expect_tx(B_PF+8*s,PST); tma2d(cb+PR+s*PST,&mp.x,s*64,m*128,B_PF+8*s); }
    asm volatile("prefetch.tensormap [%0];"::"l"(&mp.wb3):"memory"); asm volatile("prefetch.tensormap [%0];"::"l"(&mp.wb2):"memory"); }
  if(tid<256) asm volatile("st.shared.u32 [%0], %1;"::"r"(cb+SONES+tid*4),"r"(0x3F803F80u):"memory");
  fence_async_smem();
  cluster_sync();
  if(tid==0) TS(0);
  auto epoch=[&]{ mbar_wait(B_E,0); uint32_t e; asm volatile("ld.shared.u32 %0, [%1];":"=r"(e):"r"(SEP):"memory"); return e; };

  if(warp>=12){
    reg_dealloc<RP>();
    if(warp==12){
      const uint32_t tag=epoch();
      bar_sync(3,288);
      if(lane==0){
        #pragma unroll
        for(int j=0;j<2;j++){ bulk_s2g(g_kvb+((size_t)(4*hh+j)*16+m)*8192, cb+SKV+j*16384, 16384); bulk_s2g(g_kvb+((size_t)(4*hh+2+j)*16+m)*8192+4096, cb+SQ+j*8192, 8192); }
        bulk_commit(); bulk_wait<0>();
        flag_set_rlx(&g_tile[(4*hh)*16+m],tag); flag_set_rlx(&g_tile[(4*hh+1)*16+m],tag);
        mbar_arrive(B_KF); TS(18);
      }
      uint32_t ready=0;
      #pragma unroll 1
      for(int it=1;it<64;it++){ const int h=4*hh+(it>>4), t=(it+m)&15, sl=it&3;
        if((it&15)==0) ready=0;
        if(it==2) bar_sync(5,416);
        if(!((ready>>t)&1)){
          for(int i=0;;i++){ ready=__ballot_sync(0xffffffffu, ld_acq(&g_tile[h*16+(lane&15)])==tag); if((ready>>t)&1) break; if(i>(1<<22)) asm volatile("trap;"); __nanosleep(20); }
          fence_async_all(); }
        if(lane==0){
          mbar_wait(B_KE+8*sl,((it>>2)&1)^1); mbar_expect_tx(B_KF+8*sl,16384);
          bulk_g2s(cb+SKV+sl*16384, g_kvb+((size_t)h*16+t)*8192, 16384, B_KF+8*sl);
          if(it==16+NST || it==32+NST){ const int r=(it>>4)&1^1;
            flag_wait_eq(&g_tile[(h+1)*16+m],tag); fence_async_all();
            mbar_expect_tx(B_Q+8*r,8192); bulk_g2s(cb+SQ+r*8192, g_q+((size_t)(h+1)*2048+m*128)*32, 8192, B_Q+8*r); } }
        __syncwarp(); }
    } else if(warp==13){
      if(lane==0){
        const uint32_t rank=m&1;
        #pragma unroll 1
        for(int it=0;it<32;it++){ const int s=it&3, k=(it&15)*64; const uint32_t a=cb+PR+s*PST, bar=B_PF+8*s;
          if(it>=4){ mbar_wait(B_PE+8*s,((it>>2)&1)^1); mbar_expect_tx(bar,it<16 ? PST : 24576); tma2d(a,&mp.x,k,m*128,bar); }
          if(it<16) tma3d_mc(a+16384+rank*12288+4096,&mp.wb3,0,k+rank*32,32+2*hh,bar,3);
          tma2d_mc(a+16384+rank*(it<16 ? 12288 : 4096),&mp.wb2,it<16 ? 1024+hh*128 : hh*128,k+rank*32,bar,3); }
        mbar_expect_tx(B_W,8192); tma2d(cb+SW,&mp.wphi,0,hh*128,B_W);
        const uint32_t tag=epoch();
        #pragma unroll 1
        for(int it=0;it<93;it++){
          const int s=it&3; const uint32_t a=cb+SG+s*32768, bar=B_GF+8*s;
          mbar_wait(B_GE+8*s,(it>>2)&1);
          if(it<64){
            const int job=it>>4, k=(it&15)*64, n = job==0 ? rank*1024+hh*128+64 : job<3 ? 1024+rank*1024+hh*128+(job-1)*64 : hh*128+rank*64;
            mbar_expect_tx(bar,32768); tma2d_mc(a+16384+rank*8192,job==0 ? &mp.wb : &mp.wa,n,k,bar,3); tma2d(a,&mp.x,k,m*128,bar);
          } else if(it==64){
            flag_wait(&g_cnt[C_KI+hh],16*tag); fence_async_all();
            mbar_expect_tx(bar,20480); bulk_g2s(a,g_kvi+hh*1280,20480,bar);
          } else {
            const int j=it-65, k = j<8 ? 1024+j*64 : j<24 ? (j-8)*64 : 1024+(j-16)*64;
            mbar_expect_tx(bar,32768);
            if(k<1024) tma2d_mc(a+16384+rank*8192,&mp.woa,hh*128+rank*64,k,bar,3);
            else tma4d_mc(a+16384+rank*8192,&mp.wob,hh*128+rank*64,0,(k-1024)>>8,(k&255)>>5,bar,3);
            if(k==0){ flag_wait(&g_cnt[C_OA+m],8*tag); fence_async_all(); }
            if(k>=1024 && (k&255)==0){ flag_wait(&g_cnt[C_OB+((k-1024)>>8)*16+m],8*tag); fence_async_all(); }
            tma2d(a,&mp.go,k,m*128,bar);
          } }
        uint32_t todo=15;
        #pragma unroll 1
        for(int it=93;it<97;it++){
          const int s=it&3; const uint32_t a=cb+SG+s*32768, bar=B_GF+8*s;
          mbar_wait(B_GE+8*s,(it>>2)&1);
          uint32_t rdy=0;
          for(int i=0;!rdy;i++){ uint32_t c0,c1,c2,c3;
            asm volatile("ld.relaxed.gpu.global.v4.u32 {%0,%1,%2,%3}, [%4];":"=r"(c0),"=r"(c1),"=r"(c2),"=r"(c3):"l"(&g_cnt[C_OP+4*m]):"memory");
            rdy=todo&((c0==2*tag)|(c1==2*tag)<<1|(c2==2*tag)<<2|(c3==2*tag)<<3);
            if(i>(1<<22)) asm volatile("trap;"); }
          const int p=__ffs(rdy)-1; todo&=~(1u<<p);
          asm volatile("fence.acq_rel.cta;":::"memory"); fence_async_all();
          mbar_expect_tx(bar,32768);
          tma2d(a,&mp.go,1792+p*64,m*128,bar);
          tma4d(a+16384,&mp.wob,hh*128,0,3,2*p,bar); tma4d(a+24576,&mp.wob,hh*128+64,0,3,2*p,bar);
          if(it==96) TS(23); }
      }
    } else if(warp==14){
      const uint32_t tag=epoch();
      if(lane==0) flag_wait(&g_cnt[C_G+m],8*tag);
      __syncwarp();
      #pragma unroll
      for(int i=0;i<4;i++) asm volatile("st.shared.f32 [%0], %1;"::"r"(SGATE+(i*32+lane)*4),"f"(__ldcg(g_gate+m*128+i*32+lane)):"memory");
      __syncwarp(); if(lane==0) mbar_arrive(B_W+8);
      for(int r=0;r<4;r++){ bar_sync(2,288); if(lane==0){ flag_add(&g_cnt[r<3 ? C_OB+r*16+m : C_OP+4*m+(hh>>1)]); if(r==3) TS(22); } __syncwarp(); }
    } else {
      const uint32_t tag=ld_acq(&g_epoch)+1;
      if(lane==0){ asm volatile("st.shared.u32 [%0], %1;"::"r"(SEP),"r"(tag):"memory"); mbar_arrive(B_E); }
      #pragma unroll
      for(int i=0;i<5;i++) *(float4*)(g_kv+((tag+1)&1)*81920+blockIdx.x*640+i*128+lane*4)=make_float4(0.f,0.f,0.f,0.f);
      bar_sync(4,160);
      if(lane==0){
        #pragma unroll
        for(int j=0;j<2;j++){ bulk_s2g(g_q+((size_t)(4*hh+2+j)*2048+m*128)*32, cb+SG+3*32768+j*8192, 8192); bulk_s2g(g_kvb+((size_t)(4*hh+2+j)*16+m)*8192, cb+SG+3*32768+16384+j*8192, 8192); }
        bulk_commit(); bulk_wait_read<0>(); }
      __syncwarp();
      if(lane<8) mbar_arrive_cl(mapa(B_GE+24,lane&1));
      if(lane==0){ bulk_wait<0>(); flag_set_rlx(&g_tile[(4*hh+2)*16+m],tag); flag_set_rlx(&g_tile[(4*hh+3)*16+m],tag); }
      bar_sync(4,160);
      if(lane==0){ flag_add(&g_cnt[C_KV+hh]); flag_wait(&g_cnt[C_KV+hh],16*tag); }
      __syncwarp();
      const int f=m*16+(lane>>1), c0=(lane&1)*2; const float* src=g_kv+(tag&1)*81920+((size_t)hh*256+f)*40;
      #pragma unroll
      for(int c=c0;c<c0+2;c++){ const float4 a=__ldcg((const float4*)(src+c*8)), b=__ldcg((const float4*)(src+c*8+4));
        g_kvi[hh*1280+f*4+(c^((f>>1)&3))]=make_uint4(pack(a.x,a.y),pack(a.z,a.w),pack(b.x,b.y),pack(b.z,b.w)); }
      if((lane&1)==0) g_kvi[hh*1280+1024+(f&63)*4+((f>>6)^((f>>1)&3))]=make_uint4(pack(__ldcg(src+32),1.f),0u,0u,0u);
      __syncwarp();
      if(lane==0){ flag_add(&g_cnt[C_KI+hh]); }
      bar_sync(4,160);
      if(lane==0){ tma2d_store(&mp.go,cb+SG+3*32768,hh*128,m*128); tma2d_store(&mp.go,cb+SG+3*32768+16384,hh*128+64,m*128); bulk_commit(); bulk_wait_read<0>(); }
      __syncwarp();
      if(lane<8) mbar_arrive_cl(mapa(B_GE+24,lane&1));
      if(lane==0){ bulk_wait<0>(); flag_add_rlx(&g_cnt[C_OA+m]); }
    }
  } else if(warp>=8){
    reg_alloc<RG>();
    const int wq=warp-8, t128=tid-256;
    uint32_t zz; asm volatile("mov.u32 %0, 0;":"=r"(zz)); zz=__shfl_sync(0xffffffffu,zz,0);
    int s=0; uint32_t ph=0;
    const uint32_t rel=mapa(B_GE,lane&1);
    auto release=[&](int slot){ if(lane<2) mbar_arrive_cl(rel+8*slot); };
    const int srow=wq*16+(lane&15);
    {
      #pragma unroll 1
      for(int r=0;r<4;r++){ const int row=m*128+hh*16+wq*4+r; float gs=0;
        #pragma unroll
        for(int j=0;j<4;j++){ const uint4 a=__ldg((const uint4*)(mp.xp+(size_t)row*1024+j*256+lane*8)), b=__ldg((const uint4*)(mp.gw+j*256+lane*8));
          const __nv_bfloat162* pa=(const __nv_bfloat162*)&a; const __nv_bfloat162* pb=(const __nv_bfloat162*)&b;
          #pragma unroll
          for(int e=0;e<4;e++){ float2 p=__bfloat1622float2(__hmul2(pa[e],pb[e])); gs+=p.x+p.y; } }
        #pragma unroll
        for(int o=16;o;o>>=1) gs+=__shfl_xor_sync(0xffffffffu,gs,o);
        gs=__bfloat162float(__float2bfloat16(gs));
        if(lane==0) g_gate[row]=__bfloat162float(__float2bfloat16(1.f/(1.f+__expf(-gs)))); }
      bar_sync(1,128);
      if(t128==0) flag_add(&g_cnt[C_G+m]);
      bar_sync(5,416);
      #pragma unroll
      for(int i=0;i<4;i++) release(i);
    }
    #pragma unroll 1
    for(int job=-1;job<4;job++){
      float acc[2][64];
      auto stage=[&](const bool z, const bool rl){
        mbar_wait(B_GF+8*s,ph);
        const uint32_t ad=((SG+s*32768)>>4)|(1u<<16), bd=((SG+s*32768+16384)>>4)|((8192u>>4)<<16);
        #pragma unroll
        for(int kk=0;kk<4;kk++){
          if(GCG==0 || kk%(GCG?GCG:1)==0) wg_fence();
          if(z&&kk==0) wgmma_ss_n128z<0,1>(acc[0],mk_desc2(ad,HI128),mk_desc2(bd,HI128));
          else wgmma_ss_n128<0,1>(acc[0],mk_desc2(ad+kk*2,HI128),mk_desc2(bd+kk*128,HI128),1);
          if(GCG==0){ wg_commit(); wg_wait<GW>(); if(GW && rl && kk==0) release((s+3)&3); wg_fence(); }
          if(z&&kk==0) wgmma_ss_n128z<0,1>(acc[1],mk_desc2(ad+512,HI128),mk_desc2(bd,HI128));
          else wgmma_ss_n128<0,1>(acc[1],mk_desc2(ad+512+kk*2,HI128),mk_desc2(bd+kk*128,HI128),1);
          if(GCG==0 || kk%(GCG?GCG:1)==GCG-1){ wg_commit(); wg_wait<GW>(); if(rl && kk==(GW?GCG-1:3)) release(GW?(s+3)&3:s); }
        }
        s=(s+1)&3; ph^=(s==0); };
      const int nst = job==3 ? 32 : 16, nrel = job==3 ? 28+GW : 15+GW;
      stage(true,GW==0);
      #pragma unroll 1
      for(int st=1;st<nst;st++) stage(false,st<nrel);
      wg_wait<0>();
      bar_sync(1,128);
      const uint32_t SCR = SG + (job<2 ? 3*32768 : 0);
      fence_regs(acc[0]); fence_regs(acc[1]);
      if(t128==0) TS(job<0 ? 21 : 8+2*job);
      if(job<0){
        #pragma unroll
        for(int mb=0;mb<2;mb++){ const int row=mb*64+srow;
          #pragma unroll
          for(int c=0;c<8;c++){ const float* v=&acc[mb][8*c];
            stsm4(cb+SCR+(c>>1)*8192+row*64+((((c&1)*2+(lane>>4))^((row>>1)&3))<<4), pack(v[0],v[1]),pack(v[2],v[3]),pack(v[4],v[5]),pack(v[6],v[7])); } }
        fence_async_smem(); bar_arrive(4,160);
      } else if(job<2){
        if(job==0) mbar_wait(B_W,0);
        uint32_t kf[2][16];
        #pragma unroll
        for(int mb=0;mb<2;mb++){
          #pragma unroll
          for(int i=0;i<16;i++) kf[mb][i]=pack(acc[mb][2*i],acc[mb][2*i+1]);
          const int row=mb*64+srow;
          #pragma unroll
          for(int c=0;c<4;c++){ const float* v=&acc[mb][32+8*c];
            stsm4(cb+SCR+(c>>1)*8192+row*64+((((c&1)*2+(lane>>4))^((row>>1)&3))<<4), pack(v[0],v[1]),pack(v[2],v[3]),pack(v[4],v[5]),pack(v[6],v[7])); }
        }
        float pk[2][2][16];
        wg_fence();
        #pragma unroll
        for(int h=0;h<2;h++){ const uint32_t wd=((SW+(job*2+h)*2048)>>4)|(1u<<16);
          #pragma unroll
          for(int mb=0;mb<2;mb++){
            wgmma_rs_n32z<1>(pk[h][mb],kf[mb][8*h],kf[mb][8*h+1],kf[mb][8*h+2],kf[mb][8*h+3],mk_desc2(wd,HI64));
            wgmma_rs_n32<1>(pk[h][mb],kf[mb][8*h+4],kf[mb][8*h+5],kf[mb][8*h+6],kf[mb][8*h+7],mk_desc2(wd+64,HI64),1); } }
        wg_commit(); wg_wait<0>();
        float kv[20];
        auto put_kv=[&](int h){
          wg_wait<0>(); fence_regs(kv);
          float* dst=g_kv+(epoch()&1)*81920+((size_t)(4*hh+2*job+h)*64+wq*16+(lane>>2))*40+(lane&3)*2;
          #pragma unroll
          for(int j=0;j<4;j++){ red2(dst+8*j,kv[4*j],kv[4*j+1]); red2(dst+320+8*j,kv[4*j+2],kv[4*j+3]); }
          if((lane&3)==0){ red1(dst+32,kv[16]); red1(dst+352,kv[18]); } };
        #pragma unroll
        for(int h=0;h<2;h++){
          fence_regs(pk[h][0]); fence_regs(pk[h][1]);
          uint32_t ph_[2][16];
          #pragma unroll
          for(int mb=0;mb<2;mb++){
            float (&p)[16]=pk[h][mb]; float x0,x1,n0,n1; mnmx(p,x0,x1,n0,n1);
            x0*=-LOG2E; x1*=-LOG2E; n0*=LOG2E; n1*=LOG2E;
            float ep[16],en[16],sp0=0,sp1=0,sn0=0,sn1=0;
            #pragma unroll
            for(int i=0;i<16;i++){ const bool hi=i&2; ep[i]=ex2(fmaf(p[i],LOG2E,hi?x1:x0)); en[i]=ex2(fmaf(p[i],-LOG2E,hi?n1:n0));
              if(hi){ sp1+=ep[i]; sn1+=en[i]; } else { sp0+=ep[i]; sn0+=en[i]; } }
            #pragma unroll
            for(int o=1;o<4;o<<=1){ sp0+=__shfl_xor_sync(0xffffffffu,sp0,o); sp1+=__shfl_xor_sync(0xffffffffu,sp1,o); sn0+=__shfl_xor_sync(0xffffffffu,sn0,o); sn1+=__shfl_xor_sync(0xffffffffu,sn1,o); }
            sp0=rcp(sp0); sp1=rcp(sp1); sn0=rcp(sn0); sn1=rcp(sn1);
            #pragma unroll
            for(int i=0;i<8;i++){ const bool hi=i&1; ph_[mb][i]=pack(ep[2*i]*(hi?sp1:sp0),ep[2*i+1]*(hi?sp1:sp0)); ph_[mb][8+i]=pack(en[2*i]*(hi?sn1:sn0),en[2*i+1]*(hi?sn1:sn0)); }
          }
          if(h==1){
            #pragma unroll
            for(int i=0;i<16;i++) asm volatile(""::"r"(ph_[0][i]),"r"(ph_[1][i]));
            put_kv(0); bar_sync(1,128); }
          #pragma unroll
          for(int mb=0;mb<2;mb++){ const int row=mb*64+srow;
            #pragma unroll
            for(int c=0;c<4;c++) stsm4(cb+SCR+16384+row*128+(((2*c+(lane>>4))^(row&7))<<4), ph_[mb][4*c],ph_[mb][4*c+1],ph_[mb][4*c+2],ph_[mb][4*c+3]); }
          fence_async_smem(); bar_sync(1,128);
          const uint32_t pd=((SCR+16384)>>4)|(1u<<16), vd=((SCR+h*8192)>>4)|(((SONES-SCR-h*8192)>>4)<<16);
          wg_fence();
          wgmma_ss_n40z<1,1>(kv,mk_desc2(pd,HI128),mk_desc2(vd,HI64));
          #pragma unroll
          for(int ks=1;ks<8;ks++) wgmma_ss_n40<1,1>(kv,mk_desc2(pd+ks*128,HI128),mk_desc2(vd+ks*(64u-(64u<<16)),HI64),1);
          wg_commit();
        }
        put_kv(1);
        release(3);
        if(job==1) bar_arrive(4,160);
      } else if(job==2){
        uint32_t qf[2][32];
        #pragma unroll
        for(int mb=0;mb<2;mb++){
          #pragma unroll
          for(int i=0;i<32;i++) qf[mb][i]=pack(acc[mb][2*i],acc[mb][2*i+1]); }
        float pq[2][16], op[20], on[20]; uint32_t e[2][16];
        auto PQ=[&](const int i){ const int h=i>>1, mb=i&1; const uint32_t wd=((SW+h*2048)>>4)|(1u<<16);
          wgmma_rs_n32z<1>(pq[mb],qf[mb][8*h],qf[mb][8*h+1],qf[mb][8*h+2],qf[mb][8*h+3],mk_desc2(wd,HI64));
          wgmma_rs_n32<1>(pq[mb],qf[mb][8*h+4],qf[mb][8*h+5],qf[mb][8*h+6],qf[mb][8*h+7],mk_desc2(wd+64,HI64),1); };
        auto EX=[&](const int b){
          float (&p)[16]=pq[b]; fence_regs(p); float x0,x1,n0,n1; mnmx(p,x0,x1,n0,n1);
          x0*=-LOG2E; x1*=-LOG2E; n0*=LOG2E; n1*=LOG2E;
          #pragma unroll
          for(int i=0;i<8;i++){ const bool hi=i&1;
            e[b][i]=pack(ex2(fmaf(p[2*i],LOG2E,hi?x1:x0)),ex2(fmaf(p[2*i+1],LOG2E,hi?x1:x0)));
            e[b][8+i]=pack(ex2(fmaf(p[2*i],-LOG2E,hi?n1:n0)),ex2(fmaf(p[2*i+1],-LOG2E,hi?n1:n0))); }
          #pragma unroll
          for(int i=0;i<16;i++) asm volatile(""::"r"(e[b][i])); };
        wg_fence(); PQ(0); PQ(1); wg_commit(); wg_wait<0>();
        EX(0);
        mbar_wait(B_GF,ph); mbar_wait(B_W+8,0);
        float gt[4];
        #pragma unroll
        for(int i=0;i<4;i++) asm volatile("ld.shared.f32 %0, [%1];":"=f"(gt[i]):"r"(SGATE+((i>>1)*64+(i&1)*8+wq*16+(lane>>2))*4));
        #pragma unroll
        for(int i=0;i<8;i++){ const int h=i>>1, mb=i&1;
          const uint32_t kd=((SCR+h*4096)>>4)|(((16384+16*h-h*4096)>>4)<<16);
          wg_fence();
          wgmma_rs_n40z<1>(op,e[mb][0],e[mb][1],e[mb][2],e[mb][3],mk_desc2(kd,HI64));
          wgmma_rs_n40<1>(op,e[mb][4],e[mb][5],e[mb][6],e[mb][7],mk_desc2(kd+64,HI64),1);
          wgmma_rs_n40z<1>(on,e[mb][8],e[mb][9],e[mb][10],e[mb][11],mk_desc2(kd+128,HI64));
          wgmma_rs_n40<1>(on,e[mb][12],e[mb][13],e[mb][14],e[mb][15],mk_desc2(kd+192,HI64),1);
          if(i<6) PQ(i+2);
          wg_commit();
          if(i<7) EX(mb^1);
          BOUND(40+i);
          wg_wait<0>(); fence_regs(op); fence_regs(on);
          float a0=rcp(op[17]), b0=rcp(on[17]), a1=rcp(op[19]), b1=rcp(on[19]);
          const float f0=__fdividef(gt[2*mb],op[16]*a0+on[16]*b0+1e-6f), f1=__fdividef(gt[2*mb+1],op[18]*a1+on[18]*b1+1e-6f);
          a0=__shfl_sync(0xffffffffu,a0*f0,lane&28); b0=__shfl_sync(0xffffffffu,b0*f0,lane&28);
          a1=__shfl_sync(0xffffffffu,a1*f1,lane&28); b1=__shfl_sync(0xffffffffu,b1*f1,lane&28);
          const int row=mb*64+srow;
          #pragma unroll
          for(int c=0;c<2;c++){ const float* p=&op[8*c]; const float* n=&on[8*c];
            stsm4(cb+SG+3*32768+(h>>1)*16384+row*128+((((h&1)*4+c*2+(lane>>4))^(row&7))<<4),
                  pack(p[0]*a0+n[0]*b0,p[1]*a0+n[1]*b0),pack(p[2]*a1+n[2]*b1,p[3]*a1+n[3]*b1),pack(p[4]*a0+n[4]*b0,p[5]*a0+n[5]*b0),pack(p[6]*a1+n[6]*b1,p[7]*a1+n[7]*b1)); }
        }
        fence_async_smem();
        release(0); s=1;
        bar_arrive(4,160);
      } else {
        #pragma unroll
        for(int mb=0;mb<2;mb++){ const int row=mb*64+srow;
          #pragma unroll
          for(int c=0;c<8;c++){ const float* v=&acc[mb][8*c];
            stsm4(cb+SCR+(c>>2)*16384+row*128+((((c&3)*2+(lane>>4))^(row&7))<<4), pack(v[0],v[1]),pack(v[2],v[3]),pack(v[4],v[5]),pack(v[6],v[7])); } }
        fence_async_smem(); bar_sync(1,128);
        if(t128==0){ tma2d_store(&mp.out,cb+SCR,hh*128,m*128); tma2d_store(&mp.out,cb+SCR+16384,hh*128+64,m*128); bulk_commit();
          if(blockIdx.x==0) g_epoch=epoch();
          bulk_wait_read<0>(); }
      }
      if(t128==0) TS(job<0 ? 17 : 9+2*job);
    }
  } else {
    reg_alloc<RA>();
    constexpr uint32_t kd0=(SKV>>4)|(1u<<16), vd0=((SKV+8192)>>4)|(((SONES-SKV-8192)>>4)<<16);
    {
      const uint32_t prel=mapa(B_PE,lane&1); const int row=warp*16+(lane&15);
      const uint32_t so=cb+row*64, sx=(row>>1)&3;
      float acc[96];
      auto pa=[&](const int k, const bool z){
        const int ps=k&3;
        mbar_wait(B_PF+8*ps,(k>>2)&1);
        if(z && tid==0){ TS(1); TC(19); }
        const uint32_t ad=((PR+ps*PST+(warp>>2)*8192)>>4)|(1u<<16), bd=((PR+ps*PST+16384)>>4)|((4096u>>4)<<16);
        wg_fence();
        #pragma unroll
        for(int kk=0;kk<4;kk++){
          if(z&&kk==0) wgmma_ss_n192z<0,1>(acc,mk_desc2(ad,HI128),mk_desc2(bd,HI128));
          else wgmma_ss_n192<0,1>(acc,mk_desc2(ad+kk*2,HI128),mk_desc2(bd+(kk>>1)*768+(kk&1)*128,HI128),1);
          if(kk==0){ wg_commit(); wg_wait<1>(); if(!z && lane<2) mbar_arrive_cl(prel+8*((k+3)&3)); wg_fence(); } }
        wg_commit(); };
      pa(0,true);
      #pragma unroll 1
      for(int k=1;k<16;k++) pa(k,false);
      wg_wait<0>(); fence_regs(acc);
      if(lane<2) mbar_arrive_cl(prel+24);
      #pragma unroll
      for(int c=0;c<12;c++){ const float* v=&acc[8*c]; const int j=(c>>1)&1, bx=c>>2;
        stsm4(so+(bx<2 ? SKV+j*16384+bx*8192 : SQ+j*8192)+((((c&1)*2+(lane>>4))^sx)<<4), pack(v[0],v[1]),pack(v[2],v[3]),pack(v[4],v[5]),pack(v[6],v[7])); }
      fence_async_smem(); bar_arrive(3,288);
      float aq[32];
      auto pb=[&](const int k, const bool z){
        const int ps=k&3;
        mbar_wait(B_PF+8*ps,(k>>2)&1);
        const uint32_t ad=((PR+ps*PST+(warp>>2)*8192)>>4)|(1u<<16), bd=((PR+ps*PST+16384)>>4)|(1u<<16);
        wg_fence();
        #pragma unroll
        for(int kk=0;kk<4;kk++){
          if(z&&kk==0) wgmma_ss_n64z<0,1>(aq,mk_desc2(ad,HI128),mk_desc2(bd,HI128));
          else wgmma_ss_n64<0,1>(aq,mk_desc2(ad+kk*2,HI128),mk_desc2(bd+kk*128,HI128),1); }
        wg_commit(); wg_wait<0>();
        if(k<12 && lane<2) mbar_arrive_cl(prel+8*ps); };
      pb(0,true);
      #pragma unroll 1
      for(int k=1;k<16;k++) pb(k,false);
      fence_regs(aq);
      if(tid==0){ TS(2); TC(20); }
      bar_arrive(5,416);
      mbar_wait(B_KF,0);
      #pragma unroll
      for(int c=0;c<4;c++){ const float* v=&aq[8*c];
        stsm4(so+SQ+(c>>1)*8192+((((c&1)*2+(lane>>4))^sx)<<4), pack(v[0],v[1]),pack(v[2],v[3]),pack(v[4],v[5]),pack(v[6],v[7])); }
      __syncwarp();
    }
    float o[20], S0[32], S1[32], nb0=0, nb1=0; uint32_t P0[16], P1[16];
    #pragma unroll
    for(int i=0;i<20;i++) o[i]=0;
    #pragma unroll
    for(int i=0;i<16;i++) P1[i]=0;
    fence_regs(o);
    uint32_t qf[8];
    auto ldq=[&](int u){ uint32_t t; asm volatile("mov.u32 %0, %%tid.x;":"=r"(t));
      const uint32_t row=(t>>5)*16+(t&15), a=cb+SQ+(u&1)*8192+row*64;
      #pragma unroll
      for(int kk=0;kk<2;kk++) asm volatile("ldmatrix.sync.aligned.m8n8.x4.shared.b16 {%0,%1,%2,%3}, [%4];":"=r"(qf[4*kk]),"=r"(qf[4*kk+1]),"=r"(qf[4*kk+2]),"=r"(qf[4*kk+3])
        :"r"(a+(((2*kk+((t>>4)&1))^((row>>1)&3))<<4)):"memory"); };
    ldq(0);
    auto qk=[&](float (&S)[32], uint32_t kd){
      wgmma_rs_n64z<0>(S,qf[0],qf[1],qf[2],qf[3],mk_desc2(kd,HI64));
      wgmma_rs_n64<0>(S,qf[4],qf[5],qf[6],qf[7],mk_desc2(kd+2,HI64),1); };
    if(tid==0) TS(3);
    wg_fence(); qk(S0,kd0); wg_commit(); wg_wait<0>(); fence_regs(S0);
    auto epi=[&](int r){
      uint32_t cta,t; asm volatile("mov.u32 %0, %%ctaid.x;":"=r"(cta)); asm volatile("mov.u32 %0, %%tid.x;":"=r"(t));
      const int lr=(t>>5)*16+((t&31)>>2), head=4*(cta>>4)+r, ocol=1024+r*256+(cta>>4)*32;
      if(r==0) mbar_wait(B_W+8,0);
      float g0,g1; asm volatile("ld.shared.f32 %0, [%1];":"=f"(g0):"r"(SGATE+lr*4)); asm volatile("ld.shared.f32 %0, [%1];":"=f"(g1):"r"(SGATE+lr*4+32));
      g0=__bfloat162float(__float2bfloat16(1.f-g0)); g1=__bfloat162float(__float2bfloat16(1.f-g1));
      const float f0=__fdividef(g0,o[16]), f1=__fdividef(g1,o[18]);
      bf16* orow=g_o+(size_t)((cta&15)*128+lr)*2048+ocol;
      uint32_t* d=(uint32_t*)(orow+(t&3)*2);
      float t0=0,t1=0;
      #pragma unroll
      for(int j=0;j<4;j++){ d[4*j]=pack(o[4*j]*f0,o[4*j+1]*f0); d[8192+4*j]=pack(o[4*j+2]*f1,o[4*j+3]*f1);
        t0+=fabsf(o[4*j])+fabsf(o[4*j+1]); t1+=fabsf(o[4*j+2])+fabsf(o[4*j+3]); }
      const unsigned b0=__ballot_sync(0xffffffffu,!(o[16]<1e30f && t0<3e38f)), b1=__ballot_sync(0xffffffffu,!(o[18]<1e30f && t1<3e38f));
      if(b0|b1){
        const int ln=t&31; const uint8_t* kv=(const uint8_t*)(g_kvb+(size_t)head*16*8192);
        #pragma unroll 1
        for(int rr=0;rr<16;rr++){
          if(!(((rr<8?b0:b1)>>((rr&7)*4))&15)) continue;
          const int qrow=(t>>5)*16+rr; const uint32_t qa=cb+SQ+(r&1)*8192+qrow*64;
          auto dot=[&](int key){ float s=0; const uint8_t* kr=kv+(key>>7)*16384+(key&127)*64;
            #pragma unroll 1
            for(int c=0;c<4;c++){ uint4 a=__ldcg((const uint4*)(kr+((c^((key>>1)&3))<<4))), b;
              asm volatile("ld.shared.v4.u32 {%0,%1,%2,%3}, [%4];":"=r"(b.x),"=r"(b.y),"=r"(b.z),"=r"(b.w):"r"(qa+((c^((qrow>>1)&3))<<4)));
              const uint32_t* pa=&a.x; const uint32_t* pb=&b.x;
              #pragma unroll
              for(int e=0;e<4;e++){ s=fmaf(__uint_as_float(pa[e]<<16),__uint_as_float(pb[e]<<16),s); s=fmaf(__uint_as_float(pa[e]&0xffff0000u),__uint_as_float(pb[e]&0xffff0000u),s); } }
            return s; };
          float mx=-INFINITY;
          #pragma unroll 1
          for(int k=ln;k<2048;k+=32) mx=fmaxf(mx,dot(k));
          #pragma unroll
          for(int of=16;of;of>>=1) mx=fmaxf(mx,__shfl_xor_sync(0xffffffffu,mx,of));
          float a=0,l=0;
          #pragma unroll 1
          for(int k0=0;k0<2048;k0+=32){ const float p=ex2((dot(k0+ln)-mx)*SC); l+=p;
            #pragma unroll 1
            for(int j=0;j<32;j++){ const int key=k0+j; const unsigned short vv=__ldcg((const unsigned short*)(kv+(key>>7)*16384+8192+(key&127)*64+(((ln>>3)^((key>>1)&3))<<4)+(ln&7)*2));
              a=fmaf(__shfl_sync(0xffffffffu,p,j),__uint_as_float((uint32_t)vv<<16),a); } }
          #pragma unroll
          for(int of=16;of;of>>=1) l+=__shfl_xor_sync(0xffffffffu,l,of);
          float g; asm volatile("ld.shared.f32 %0, [%1];":"=f"(g):"r"(SGATE+qrow*4));
          g=__bfloat162float(__float2bfloat16(1.f-g));
          __syncwarp();
          g_o[(size_t)((cta&15)*128+qrow)*2048+ocol+ln]=__float2bfloat16(a*g/l);
        }
      }
      bar_arrive(2,288);
      if(t==0){ TS(4+r); if(r==3) TC(16); }
    };
    const bool l0 = lane==0;
    uint32_t zz; asm volatile("mov.u32 %0, 0;":"=r"(zz)); zz=__shfl_sync(0xffffffffu,zz,0);
    uint32_t sp=NST-1, sc=0, sn=1, phn=0;
    auto newmax=[&](float (&S)[32]){
      float m0=S[0],m1=S[2];
      #pragma unroll
      for(int i=0;i<8;i++){ m0=fmaxf(m0,fmaxf(S[4*i],S[4*i+1])); m1=fmaxf(m1,fmaxf(S[4*i+2],S[4*i+3])); }
      m0=fmaxf(m0,__shfl_xor_sync(0xffffffffu,m0,1)); m0=fmaxf(m0,__shfl_xor_sync(0xffffffffu,m0,2));
      m1=fmaxf(m1,__shfl_xor_sync(0xffffffffu,m1,1)); m1=fmaxf(m1,__shfl_xor_sync(0xffffffffu,m1,2));
      nb0=-(m0*SC+OFFS); nb1=-(m1*SC+OFFS); };
    newmax(S0);
    #pragma unroll
    for(int i=0;i<32;i++) S0[i]=fmaf(S0[i],SC,((i>>1)&1)?nb1:nb0);
    auto step=[&](const int r, const int MODE, const int U, float (&S)[32], uint32_t (&P)[16], float (&Sn)[32], uint32_t (&Pp)[16]){
      const bool first=(U==0)&&MODE==1, second=(U==1)&&MODE==1, last=(U==1)&&MODE==2;
      if(second && r>0) epi(r-1);
      if(last){ if(r==1 || r==2) mbar_wait(B_Q+8*((r+1)&1),0); ldq(r+1); }
      const uint32_t vd= U==0 ? vd0+sp*(1024u-(1024u<<16))+4*(64u-(64u<<16)) : vd0+sc*(1024u-(1024u<<16));
      const uint32_t kd= U==0 ? kd0+sc*1024u+256u : kd0+sn*1024u;
      bool ok=true;
      if(U==0 && !(MODE==2 && r==3)) ok=mbar_try(B_KF+8*sn, phn);
      wg_fence();
      qk(Sn,kd);
      #pragma unroll
      for(int kk=0;kk<4;kk++){
        if(second&&kk==0) wgmma_rs_n40z<1>(o,Pp[4*kk],Pp[4*kk+1],Pp[4*kk+2],Pp[4*kk+3],mk_desc2(vd+kk*(64u-(64u<<16)),HI64));
        else wgmma_rs_n40<1>(o,Pp[4*kk],Pp[4*kk+1],Pp[4*kk+2],Pp[4*kk+3],mk_desc2(vd+kk*(64u-(64u<<16)),HI64),1); }
      wg_commit();
      #pragma unroll
      for(int i=0;i<PA;i++) P[i]=pack(ex2(S[2*i]),ex2(S[2*i+1]));
      #pragma unroll
      for(int i=0;i<PA;i++) asm volatile(""::"r"(P[i]));
      if(U==0){ if(__builtin_expect(!ok,0)) mbar_wait(B_KF+8*sn, phn); } else BOUND(1+MODE*8);
      #pragma unroll
      for(int i=PA;i<PART;i++) P[i]=pack(ex2(S[2*i]),ex2(S[2*i+1]));
      #pragma unroll
      for(int i=PA;i<PART;i++) asm volatile(""::"r"(P[i]));
      BOUND(2+U+MODE*8);
      wg_wait<0>(); fence_regs(Sn); fence_regs(o);
      if(last) newmax(Sn);
      #pragma unroll
      for(int i=PART;i<16;i++){
        #pragma unroll
        for(int j=(i-PART)*32/(16-PART);j<(i+1-PART)*32/(16-PART);j++) Sn[j]=fmaf(Sn[j],SC,((j>>1)&1)?nb1:nb0);
        P[i]=pack(ex2(S[2*i]),ex2(S[2*i+1])); }
      fence_regs(Sn);
      if(U==0){ if(l0 && !(first && r==0)) mbar_arrive(B_KE+8*sp); }
      else { sp=sc; sc=sn; sn=sn+1==NST?0:sn+1; phn^=(sn==0); }
    };
    #pragma unroll 1
    for(int r=0;r<4;r++){
      step(r,1,0,S0,P0,S1,P1); step(r,1,1,S1,P1,S0,P0);
      #pragma unroll 1
      for(int t=0;t<14;t++){ step(r,0,0,S0,P0,S1,P1); step(r,0,1,S1,P1,S0,P0); }
      step(r,2,0,S0,P0,S1,P1); step(r,2,1,S1,P1,S0,P0);
    }
    { const uint32_t vd=vd0+sp*(1024u-(1024u<<16))+4*(64u-(64u<<16));
      wg_fence();
      #pragma unroll
      for(int kk=0;kk<4;kk++) wgmma_rs_n40<1>(o,P1[4*kk],P1[4*kk+1],P1[4*kk+2],P1[4*kk+3],mk_desc2(vd+kk*(64u-(64u<<16)),HI64),1);
      wg_commit(); }
    wg_wait<0>(); fence_regs(o);
    epi(3);
  }
}

typedef CUresult (*PFN_enc)(CUtensorMap*, CUtensorMapDataType, cuuint32_t, void*, const cuuint64_t*, const cuuint64_t*, const cuuint32_t*, const cuuint32_t*, CUtensorMapInterleave, CUtensorMapSwizzle, CUtensorMapL2promotion, CUtensorMapFloatOOBfill);
static CUtensorMap mk_map(PFN_enc fn, const void* p, int rank, const cuuint64_t* dims, const cuuint64_t* strides, const cuuint32_t* box, CUtensorMapSwizzle sw){
  CUtensorMap m; cuuint32_t es[4]={1,1,1,1};
  fn(&m, CU_TENSOR_MAP_DATA_TYPE_BFLOAT16, rank, (void*)p, dims, strides, box, es, CU_TENSOR_MAP_INTERLEAVE_NONE, sw, CU_TENSOR_MAP_L2_PROMOTION_L2_256B, CU_TENSOR_MAP_FLOAT_OOB_FILL_NONE);
  return m; }
static CUtensorMap map2d(PFN_enc fn, const void* p, uint64_t inner, uint64_t outer, uint32_t bi, uint32_t bo, CUtensorMapSwizzle sw){
  cuuint64_t d[2]={inner,outer}, s[1]={inner*2}; cuuint32_t b[2]={bi,bo}; return mk_map(fn,p,2,d,s,b,sw); }

extern "C" void kernel_launch(void* const* d_in, const int* in_sizes, int n_in, void* d_out, int out_size){
  static bool init=false; static Maps mp; static const void* key[8];
  const void* cur[8]={d_in[0],d_in[1],d_in[2],d_in[3],d_in[5],d_in[6],d_in[7],d_out};
  bool same=init; for(int i=0;i<8;i++) same = same && key[i]==cur[i];
  if(!same){
    PFN_enc fn=nullptr; cudaDriverEntryPointQueryResult q; cudaGetDriverEntryPoint("cuTensorMapEncodeTiled",(void**)&fn,cudaEnableDefault,&q);
    void* go; cudaGetSymbolAddress(&go,g_o);
    const CUtensorMapSwizzle S128=CU_TENSOR_MAP_SWIZZLE_128B;
    mp.x=map2d(fn,d_in[0],1024,2048,64,128,S128);
    mp.wa=map2d(fn,d_in[1],3072,1024,64,64,S128);
    mp.wb=map2d(fn,d_in[5],3072,1024,64,64,S128);
    mp.wb2=map2d(fn,d_in[5],3072,1024,64,32,S128);
    { cuuint64_t d[3]={64,1024,48}, s[2]={6144,128}; cuuint32_t b[3]={64,32,2}; mp.wb3=mk_map(fn,d_in[5],3,d,s,b,S128); }
    mp.go=map2d(fn,go,2048,2048,64,128,S128);
    mp.woa=map2d(fn,d_in[3],1024,1024,64,64,S128);
    { cuuint64_t d[4]={1024,32,4,8}, s[3]={2048,65536,262144}; cuuint32_t b[4]={64,32,1,2}; mp.wob=mk_map(fn,d_in[6],4,d,s,b,S128); }
    mp.out=map2d(fn,d_out,1024,2048,64,128,S128);
    mp.wphi=map2d(fn,d_in[2],32,1024,32,128,CU_TENSOR_MAP_SWIZZLE_64B);
    mp.xp=(const bf16*)d_in[0]; mp.gw=(const bf16*)d_in[7];
    cudaFuncSetAttribute(k_main,cudaFuncAttributeMaxDynamicSharedMemorySize,k2::SMEM);
    for(int i=0;i<8;i++) key[i]=cur[i];
    init=true;
  }
  cudaLaunchConfig_t cfg={}; cfg.gridDim=128; cfg.blockDim=512; cfg.dynamicSmemBytes=k2::SMEM; cfg.stream=cudaStreamPerThread;
  cudaLaunchAttribute at[1];
  at[0].id=cudaLaunchAttributeClusterDimension; at[0].val.clusterDim.x=2; at[0].val.clusterDim.y=1; at[0].val.clusterDim.z=1;
  cfg.attrs=at; cfg.numAttrs=1;
  cudaLaunchKernelEx(&cfg,k_main,mp);
}
```

```cpp
#include <cuda_runtime.h>
#include <cuda_bf16.h>
#include <cuda.h>
#include <stdint.h>

typedef __nv_bfloat16 bf16;
#define DEVI __device__ __forceinline__

DEVI uint32_t smem_u32(const void* p){ return (uint32_t)__cvta_generic_to_shared(p); }
DEVI void mbar_init(uint32_t bar, uint32_t cnt){ asm volatile("mbarrier.init.shared::cta.b64 [%0], %1;"::"r"(bar),"r"(cnt):"memory"); }
DEVI void mbar_expect_tx(uint32_t bar, uint32_t bytes){ asm volatile("mbarrier.arrive.expect_tx.shared::cta.b64 _, [%0], %1;"::"r"(bar),"r"(bytes):"memory"); }
DEVI void mbar_arrive(uint32_t bar){ asm volatile("mbarrier.arrive.shared::cta.b64 _, [%0];"::"r"(bar):"memory"); }
DEVI bool mbar_try(uint32_t bar, uint32_t parity){ uint32_t ok;
  asm volatile("{\n.reg .pred p;\nmbarrier.try_wait.parity.shared::cta.b64 p, [%1], %2;\nselp.u32 %0, 1, 0, p;\n}\n":"=r"(ok):"r"(bar),"r"(parity):"memory"); return ok; }
DEVI void mbar_wait(uint32_t bar, uint32_t parity){
  asm volatile("{\n.reg .pred p;\n.reg .u32 c;\nmov.u32 c, 0;\nLAB_WAIT:\nmbarrier.try_wait.parity.shared::cta.b64 p, [%0], %1;\n@p bra DONE;\nadd.u32 c, c, 1;\nsetp.lt.u32 p, c, 0x200000;\n@p bra LAB_WAIT;\ntrap;\nDONE:\n}\n"::"r"(bar),"r"(parity):"memory"); }
DEVI void tma2d(uint32_t dst, const CUtensorMap* m, int c0, int c1, uint32_t bar){
  asm volatile("cp.async.bulk.tensor.2d.shared::cluster.global.mbarrier::complete_tx::bytes [%0], [%1, {%3, %4}], [%2];"::"r"(dst),"l"(m),"r"(bar),"r"(c0),"r"(c1):"memory"); }
DEVI void tma2d_mc(uint32_t dst, const CUtensorMap* m, int c0, int c1, uint32_t bar, uint16_t mask){
  asm volatile("cp.async.bulk.tensor.2d.shared::cluster.global.mbarrier::complete_tx::bytes.multicast::cluster [%0], [%1, {%3, %4}], [%2], %5;"::"r"(dst),"l"(m),"r"(bar),"r"(c0),"r"(c1),"h"(mask):"memory"); }
DEVI void tma3d_mc(uint32_t dst, const CUtensorMap* m, int c0, int c1, int c2, uint32_t bar, uint16_t mask){
  asm volatile("cp.async.bulk.tensor.3d.shared::cluster.global.mbarrier::complete_tx::bytes.multicast::cluster [%0], [%1, {%3, %4, %5}], [%2], %6;"::"r"(dst),"l"(m),"r"(bar),"r"(c0),"r"(c1),"r"(c2),"h"(mask):"memory"); }
DEVI void tma4d_mc(uint32_t dst, const CUtensorMap* m, int c0, int c1, int c2, int c3, uint32_t bar, uint16_t mask){
  asm volatile("cp.async.bulk.tensor.4d.shared::cluster.global.mbarrier::complete_tx::bytes.multicast::cluster [%0], [%1, {%3, %4, %5, %6}], [%2], %7;"::"r"(dst),"l"(m),"r"(bar),"r"(c0),"r"(c1),"r"(c2),"r"(c3),"h"(mask):"memory"); }
DEVI void tma4d(uint32_t dst, const CUtensorMap* m, int c0, int c1, int c2, int c3, uint32_t bar){
  asm volatile("cp.async.bulk.tensor.4d.shared::cluster.global.mbarrier::complete_tx::bytes [%0], [%1, {%3, %4, %5, %6}], [%2];"::"r"(dst),"l"(m),"r"(bar),"r"(c0),"r"(c1),"r"(c2),"r"(c3):"memory"); }
DEVI uint32_t mapa(uint32_t a, uint32_t rank){ uint32_t r; asm("mapa.shared::cluster.u32 %0, %1, %2;":"=r"(r):"r"(a),"r"(rank)); return r; }
DEVI void mbar_arrive_cl(uint32_t a){ asm volatile("mbarrier.arrive.shared::cluster.b64 _, [%0];"::"r"(a):"memory"); }
DEVI void cluster_sync(){ asm volatile("barrier.cluster.arrive.relaxed.aligned;\nbarrier.cluster.wait.acquire.aligned;":::"memory"); }
DEVI void tma3d(uint32_t dst, const CUtensorMap* m, int c0, int c1, int c2, uint32_t bar){
  asm volatile("cp.async.bulk.tensor.3d.shared::cluster.global.mbarrier::complete_tx::bytes [%0], [%1, {%3, %4, %5}], [%2];"::"r"(dst),"l"(m),"r"(bar),"r"(c0),"r"(c1),"r"(c2):"memory"); }
DEVI void tma2d_store(const CUtensorMap* m, uint32_t src, int c0, int c1){
  asm volatile("cp.async.bulk.tensor.2d.global.shared::cta.bulk_group [%0, {%2, %3}], [%1];"::"l"(m),"r"(src),"r"(c0),"r"(c1):"memory"); }
DEVI void bulk_g2s(uint32_t dst, const void* src, uint32_t bytes, uint32_t bar){
  asm volatile("cp.async.bulk.shared::cluster.global.mbarrier::complete_tx::bytes [%0], [%1], %2, [%3];"::"r"(dst),"l"(src),"r"(bytes),"r"(bar):"memory"); }
DEVI void bulk_s2g(void* dst, uint32_t src, uint32_t bytes){
  asm volatile("cp.async.bulk.global.shared::cta.bulk_group [%0], [%1], %2;"::"l"(dst),"r"(src),"r"(bytes):"memory"); }
DEVI void bulk_commit(){ asm volatile("cp.async.bulk.commit_group;":::"memory"); }
template<int N> DEVI void bulk_wait(){ asm volatile("cp.async.bulk.wait_group %0;"::"n"(N):"memory"); }
template<int N> DEVI void bulk_wait_read(){ asm volatile("cp.async.bulk.wait_group.read %0;"::"n"(N):"memory"); }
DEVI void fence_async_smem(){ asm volatile("fence.proxy.async.shared::cta;":::"memory"); }
DEVI void fence_async_all(){ asm volatile("fence.proxy.async.global;":::"memory"); }
DEVI void wg_fence(){ asm volatile("wgmma.fence.sync.aligned;":::"memory"); }
DEVI void wg_commit(){ asm volatile("wgmma.commit_group.sync.aligned;":::"memory"); }
template<int N> DEVI void wg_wait(){ asm volatile("wgmma.wait_group.sync.aligned %0;"::"n"(N):"memory"); }
DEVI uint64_t mk_desc2(uint32_t lo, uint32_t hi){ uint64_t d; asm("mov.b64 %0, {%1,%2};":"=l"(d):"r"(lo),"r"(hi)); return d; }
template<int R> DEVI void reg_alloc(){ asm volatile("setmaxnreg.inc.sync.aligned.u32 %0;"::"n"(R)); }
template<int R> DEVI void reg_dealloc(){ asm volatile("setmaxnreg.dec.sync.aligned.u32 %0;"::"n"(R)); }
template<int N> DEVI void fence_regs(float (&r)[N]){
  #pragma unroll
  for(int i=0;i<N;i++) asm volatile("":"+f"(r[i])::"memory"); }
DEVI void griddep_wait(){ asm volatile("griddepcontrol.wait;":::"memory"); }
DEVI void bar_sync(int id, int n){ asm volatile("bar.sync %0, %1;"::"r"(id),"r"(n):"memory"); }
DEVI void bar_arrive(int id, int n){ asm volatile("bar.arrive %0, %1;"::"r"(id),"r"(n):"memory"); }
DEVI float ex2(float x){ float y; asm("ex2.approx.ftz.f32 %0,%1;":"=f"(y):"f"(x)); return y; }
DEVI float rcp(float x){ float y; asm("rcp.approx.ftz.f32 %0,%1;":"=f"(y):"f"(x)); return y; }
DEVI uint32_t pack(float lo,float hi){ uint32_t y; asm("cvt.rn.bf16x2.f32 %0,%1,%2;":"=r"(y):"f"(hi),"f"(lo)); return y; }
DEVI void stsm4(uint32_t a, uint32_t r0, uint32_t r1, uint32_t r2, uint32_t r3){
  asm volatile("stmatrix.sync.aligned.m8n8.x4.shared.b16 [%0], {%1,%2,%3,%4};"::"r"(a),"r"(r0),"r"(r1),"r"(r2),"r"(r3):"memory"); }
DEVI void flag_add(unsigned* p){ asm volatile("fence.acq_rel.gpu;\nred.relaxed.gpu.global.add.u32 [%0], 1;"::"l"(p):"memory"); }
DEVI unsigned ld_acq(const unsigned* p){ unsigned v; asm volatile("ld.acquire.gpu.global.u32 %0, [%1];":"=r"(v):"l"(p):"memory"); return v; }
DEVI void flag_set(unsigned* p, unsigned v){ asm volatile("st.release.gpu.global.u32 [%0], %1;"::"l"(p),"r"(v):"memory"); }
DEVI void flag_set_rlx(unsigned* p, unsigned v){ asm volatile("fence.proxy.async.global;\nst.relaxed.gpu.global.u32 [%0], %1;"::"l"(p),"r"(v):"memory"); }
DEVI void flag_add_rlx(unsigned* p){ asm volatile("fence.proxy.async.global;\nred.relaxed.gpu.global.add.u32 [%0], 1;"::"l"(p):"memory"); }
DEVI void flag_wait(const unsigned* p, unsigned target){
  for(int i=0;i<(1<<22);i++){ if((int)(ld_acq(p)-target)>=0) return; __nanosleep(40); }
  asm volatile("trap;"); }
DEVI void flag_wait_eq(const unsigned* p, unsigned tag){
  for(int i=0;i<(1<<22);i++){ if(ld_acq(p)==tag) return; __nanosleep(40); }
  asm volatile("trap;"); }
DEVI void red2(float* p, float a, float b){ asm volatile("red.relaxed.gpu.global.add.v2.f32 [%0], {%1,%2};"::"l"(p),"f"(a),"f"(b):"memory"); }
DEVI void red1(float* p, float a){ asm volatile("red.relaxed.gpu.global.add.f32 [%0], %1;"::"l"(p),"f"(a):"memory"); }
#define BOUND(c) asm volatile("{\n.reg .pred p;\nsetp.eq.u32 p, %0, %1;\n@p exit;\n}\n"::"r"(zz),"r"(c):"memory")
template<int TB> DEVI void wgmma_rs_n128(float (&d)[64], uint32_t a0, uint32_t a1, uint32_t a2, uint32_t a3, uint64_t db, int sd){
  asm volatile("{\n.reg .pred p;\nsetp.ne.b32 p, %69, 0;\n"
    "wgmma.mma_async.sync.aligned.m64n128k16.f32.bf16.bf16 {%0, %1, %2, %3, %4, %5, %6, %7, %8, %9, %10, %11, %12, %13, %14, %15, %16, %17, %18, %19, %20, %21, %22, %23, %24, %25, %26, %27, %28, %29, %30, %31, %32, %33, %34, %35, %36, %37, %38, %39, %40, %41, %42, %43, %44, %45, %46, %47, %48, %49, %50, %51, %52, %53, %54, %55, %56, %57, %58, %59, %60, %61, %62, %63}, {%64,%65,%66,%67}, %68, p, 1, 1, %70;\n}\n"
    : "+f"(d[0]), "+f"(d[1]), "+f"(d[2]), "+f"(d[3]), "+f"(d[4]), "+f"(d[5]), "+f"(d[6]), "+f"(d[7]), "+f"(d[8]), "+f"(d[9]), "+f"(d[10]), "+f"(d[11]), "+f"(d[12]), "+f"(d[13]), "+f"(d[14]), "+f"(d[15]), "+f"(d[16]), "+f"(d[17]), "+f"(d[18]), "+f"(d[19]), "+f"(d[20]), "+f"(d[21]), "+f"(d[22]), "+f"(d[23]), "+f"(d[24]), "+f"(d[25]), "+f"(d[26]), "+f"(d[27]), "+f"(d[28]), "+f"(d[29]), "+f"(d[30]), "+f"(d[31]), "+f"(d[32]), "+f"(d[33]), "+f"(d[34]), "+f"(d[35]), "+f"(d[36]), "+f"(d[37]), "+f"(d[38]), "+f"(d[39]), "+f"(d[40]), "+f"(d[41]), "+f"(d[42]), "+f"(d[43]), "+f"(d[44]), "+f"(d[45]), "+f"(d[46]), "+f"(d[47]), "+f"(d[48]), "+f"(d[49]), "+f"(d[50]), "+f"(d[51]), "+f"(d[52]), "+f"(d[53]), "+f"(d[54]), "+f"(d[55]), "+f"(d[56]), "+f"(d[57]), "+f"(d[58]), "+f"(d[59]), "+f"(d[60]), "+f"(d[61]), "+f"(d[62]), "+f"(d[63])
    : "r"(a0), "r"(a1), "r"(a2), "r"(a3), "l"(db), "r"(sd), "n"(TB));
}
template<int TB> DEVI void wgmma_rs_n128z(float (&d)[64], uint32_t a0, uint32_t a1, uint32_t a2, uint32_t a3, uint64_t db){
  asm volatile("{\n.reg .pred p;\nsetp.ne.b32 p, 0, 0;\n"
    "wgmma.mma_async.sync.aligned.m64n128k16.f32.bf16.bf16 {%0, %1, %2, %3, %4, %5, %6, %7, %8, %9, %10, %11, %12, %13, %14, %15, %16, %17, %18, %19, %20, %21, %22, %23, %24, %25, %26, %27, %28, %29, %30, %31, %32, %33, %34, %35, %36, %37, %38, %39, %40, %41, %42, %43, %44, %45, %46, %47, %48, %49, %50, %51, %52, %53, %54, %55, %56, %57, %58, %59, %60, %61, %62, %63}, {%64,%65,%66,%67}, %68, p, 1, 1, %69;\n}\n"
    : "=f"(d[0]), "=f"(d[1]), "=f"(d[2]), "=f"(d[3]), "=f"(d[4]), "=f"(d[5]), "=f"(d[6]), "=f"(d[7]), "=f"(d[8]), "=f"(d[9]), "=f"(d[10]), "=f"(d[11]), "=f"(d[12]), "=f"(d[13]), "=f"(d[14]), "=f"(d[15]), "=f"(d[16]), "=f"(d[17]), "=f"(d[18]), "=f"(d[19]), "=f"(d[20]), "=f"(d[21]), "=f"(d[22]), "=f"(d[23]), "=f"(d[24]), "=f"(d[25]), "=f"(d[26]), "=f"(d[27]), "=f"(d[28]), "=f"(d[29]), "=f"(d[30]), "=f"(d[31]), "=f"(d[32]), "=f"(d[33]), "=f"(d[34]), "=f"(d[35]), "=f"(d[36]), "=f"(d[37]), "=f"(d[38]), "=f"(d[39]), "=f"(d[40]), "=f"(d[41]), "=f"(d[42]), "=f"(d[43]), "=f"(d[44]), "=f"(d[45]), "=f"(d[46]), "=f"(d[47]), "=f"(d[48]), "=f"(d[49]), "=f"(d[50]), "=f"(d[51]), "=f"(d[52]), "=f"(d[53]), "=f"(d[54]), "=f"(d[55]), "=f"(d[56]), "=f"(d[57]), "=f"(d[58]), "=f"(d[59]), "=f"(d[60]), "=f"(d[61]), "=f"(d[62]), "=f"(d[63])
    : "r"(a0), "r"(a1), "r"(a2), "r"(a3), "l"(db), "n"(TB));
}
template<int TA, int TB> DEVI void wgmma_ss_n128(float (&d)[64], uint64_t da, uint64_t db, int sd){
  asm volatile("{\n.reg .pred p;\nsetp.ne.b32 p, %66, 0;\n"
    "wgmma.mma_async.sync.aligned.m64n128k16.f32.bf16.bf16 {%0, %1, %2, %3, %4, %5, %6, %7, %8, %9, %10, %11, %12, %13, %14, %15, %16, %17, %18, %19, %20, %21, %22, %23, %24, %25, %26, %27, %28, %29, %30, %31, %32, %33, %34, %35, %36, %37, %38, %39, %40, %41, %42, %43, %44, %45, %46, %47, %48, %49, %50, %51, %52, %53, %54, %55, %56, %57, %58, %59, %60, %61, %62, %63}, %64, %65, p, 1, 1, %67, %68;\n}\n"
    : "+f"(d[0]), "+f"(d[1]), "+f"(d[2]), "+f"(d[3]), "+f"(d[4]), "+f"(d[5]), "+f"(d[6]), "+f"(d[7]), "+f"(d[8]), "+f"(d[9]), "+f"(d[10]), "+f"(d[11]), "+f"(d[12]), "+f"(d[13]), "+f"(d[14]), "+f"(d[15]), "+f"(d[16]), "+f"(d[17]), "+f"(d[18]), "+f"(d[19]), "+f"(d[20]), "+f"(d[21]), "+f"(d[22]), "+f"(d[23]), "+f"(d[24]), "+f"(d[25]), "+f"(d[26]), "+f"(d[27]), "+f"(d[28]), "+f"(d[29]), "+f"(d[30]), "+f"(d[31]), "+f"(d[32]), "+f"(d[33]), "+f"(d[34]), "+f"(d[35]), "+f"(d[36]), "+f"(d[37]), "+f"(d[38]), "+f"(d[39]), "+f"(d[40]), "+f"(d[41]), "+f"(d[42]), "+f"(d[43]), "+f"(d[44]), "+f"(d[45]), "+f"(d[46]), "+f"(d[47]), "+f"(d[48]), "+f"(d[49]), "+f"(d[50]), "+f"(d[51]), "+f"(d[52]), "+f"(d[53]), "+f"(d[54]), "+f"(d[55]), "+f"(d[56]), "+f"(d[57]), "+f"(d[58]), "+f"(d[59]), "+f"(d[60]), "+f"(d[61]), "+f"(d[62]), "+f"(d[63])
    : "l"(da), "l"(db), "r"(sd), "n"(TA), "n"(TB));
}
template<int TA, int TB> DEVI void wgmma_ss_n128z(float (&d)[64], uint64_t da, uint64_t db){
  asm volatile("{\n.reg .pred p;\nsetp.ne.b32 p, 0, 0;\n"
    "wgmma.mma_async.sync.aligned.m64n128k16.f32.bf16.bf16 {%0, %1, %2, %3, %4, %5, %6, %7, %8, %9, %10, %11, %12, %13, %14, %15, %16, %17, %18, %19, %20, %21, %22, %23, %24, %25, %26, %27, %28, %29, %30, %31, %32, %33, %34, %35, %36, %37, %38, %39, %40, %41, %42, %43, %44, %45, %46, %47, %48, %49, %50, %51, %52, %53, %54, %55, %56, %57, %58, %59, %60, %61, %62, %63}, %64, %65, p, 1, 1, %66, %67;\n}\n"
    : "=f"(d[0]), "=f"(d[1]), "=f"(d[2]), "=f"(d[3]), "=f"(d[4]), "=f"(d[5]), "=f"(d[6]), "=f"(d[7]), "=f"(d[8]), "=f"(d[9]), "=f"(d[10]), "=f"(d[11]), "=f"(d[12]), "=f"(d[13]), "=f"(d[14]), "=f"(d[15]), "=f"(d[16]), "=f"(d[17]), "=f"(d[18]), "=f"(d[19]), "=f"(d[20]), "=f"(d[21]), "=f"(d[22]), "=f"(d[23]), "=f"(d[24]), "=f"(d[25]), "=f"(d[26]), "=f"(d[27]), "=f"(d[28]), "=f"(d[29]), "=f"(d[30]), "=f"(d[31]), "=f"(d[32]), "=f"(d[33]), "=f"(d[34]), "=f"(d[35]), "=f"(d[36]), "=f"(d[37]), "=f"(d[38]), "=f"(d[39]), "=f"(d[40]), "=f"(d[41]), "=f"(d[42]), "=f"(d[43]), "=f"(d[44]), "=f"(d[45]), "=f"(d[46]), "=f"(d[47]), "=f"(d[48]), "=f"(d[49]), "=f"(d[50]), "=f"(d[51]), "=f"(d[52]), "=f"(d[53]), "=f"(d[54]), "=f"(d[55]), "=f"(d[56]), "=f"(d[57]), "=f"(d[58]), "=f"(d[59]), "=f"(d[60]), "=f"(d[61]), "=f"(d[62]), "=f"(d[63])
    : "l"(da), "l"(db), "n"(TA), "n"(TB));
}
template<int TB> DEVI void wgmma_rs_n40(float (&d)[20], uint32_t a0, uint32_t a1, uint32_t a2, uint32_t a3, uint64_t db, int sd){
  asm volatile("{\n.reg .pred p;\nsetp.ne.b32 p, %25, 0;\n"
    "wgmma.mma_async.sync.aligned.m64n40k16.f32.bf16.bf16 {%0, %1, %2, %3, %4, %5, %6, %7, %8, %9, %10, %11, %12, %13, %14, %15, %16, %17, %18, %19}, {%20,%21,%22,%23}, %24, p, 1, 1, %26;\n}\n"
    : "+f"(d[0]), "+f"(d[1]), "+f"(d[2]), "+f"(d[3]), "+f"(d[4]), "+f"(d[5]), "+f"(d[6]), "+f"(d[7]), "+f"(d[8]), "+f"(d[9]), "+f"(d[10]), "+f"(d[11]), "+f"(d[12]), "+f"(d[13]), "+f"(d[14]), "+f"(d[15]), "+f"(d[16]), "+f"(d[17]), "+f"(d[18]), "+f"(d[19])
    : "r"(a0), "r"(a1), "r"(a2), "r"(a3), "l"(db), "r"(sd), "n"(TB));
}
template<int TB> DEVI void wgmma_rs_n40z(float (&d)[20], uint32_t a0, uint32_t a1, uint32_t a2, uint32_t a3, uint64_t db){
  asm volatile("{\n.reg .pred p;\nsetp.ne.b32 p, 0, 0;\n"
    "wgmma.mma_async.sync.aligned.m64n40k16.f32.bf16.bf16 {%0, %1, %2, %3, %4, %5, %6, %7, %8, %9, %10, %11, %12, %13, %14, %15, %16, %17, %18, %19}, {%20,%21,%22,%23}, %24, p, 1, 1, %25;\n}\n"
    : "=f"(d[0]), "=f"(d[1]), "=f"(d[2]), "=f"(d[3]), "=f"(d[4]), "=f"(d[5]), "=f"(d[6]), "=f"(d[7]), "=f"(d[8]), "=f"(d[9]), "=f"(d[10]), "=f"(d[11]), "=f"(d[12]), "=f"(d[13]), "=f"(d[14]), "=f"(d[15]), "=f"(d[16]), "=f"(d[17]), "=f"(d[18]), "=f"(d[19])
    : "r"(a0), "r"(a1), "r"(a2), "r"(a3), "l"(db), "n"(TB));
}
template<int TA, int TB> DEVI void wgmma_ss_n40(float (&d)[20], uint64_t da, uint64_t db, int sd){
  asm volatile("{\n.reg .pred p;\nsetp.ne.b32 p, %22, 0;\n"
    "wgmma.mma_async.sync.aligned.m64n40k16.f32.bf16.bf16 {%0, %1, %2, %3, %4, %5, %6, %7, %8, %9, %10, %11, %12, %13, %14, %15, %16, %17, %18, %19}, %20, %21, p, 1, 1, %23, %24;\n}\n"
    : "+f"(d[0]), "+f"(d[1]), "+f"(d[2]), "+f"(d[3]), "+f"(d[4]), "+f"(d[5]), "+f"(d[6]), "+f"(d[7]), "+f"(d[8]), "+f"(d[9]), "+f"(d[10]), "+f"(d[11]), "+f"(d[12]), "+f"(d[13]), "+f"(d[14]), "+f"(d[15]), "+f"(d[16]), "+f"(d[17]), "+f"(d[18]), "+f"(d[19])
    : "l"(da), "l"(db), "r"(sd), "n"(TA), "n"(TB));
}
template<int TA, int TB> DEVI void wgmma_ss_n40z(float (&d)[20], uint64_t da, uint64_t db){
  asm volatile("{\n.reg .pred p;\nsetp.ne.b32 p, 0, 0;\n"
    "wgmma.mma_async.sync.aligned.m64n40k16.f32.bf16.bf16 {%0, %1, %2, %3, %4, %5, %6, %7, %8, %9, %10, %11, %12, %13, %14, %15, %16, %17, %18, %19}, %20, %21, p, 1, 1, %22, %23;\n}\n"
    : "=f"(d[0]), "=f"(d[1]), "=f"(d[2]), "=f"(d[3]), "=f"(d[4]), "=f"(d[5]), "=f"(d[6]), "=f"(d[7]), "=f"(d[8]), "=f"(d[9]), "=f"(d[10]), "=f"(d[11]), "=f"(d[12]), "=f"(d[13]), "=f"(d[14]), "=f"(d[15]), "=f"(d[16]), "=f"(d[17]), "=f"(d[18]), "=f"(d[19])
    : "l"(da), "l"(db), "n"(TA), "n"(TB));
}
template<int TB> DEVI void wgmma_rs_n32(float (&d)[16], uint32_t a0, uint32_t a1, uint32_t a2, uint32_t a3, uint64_t db, int sd){
  asm volatile("{\n.reg .pred p;\nsetp.ne.b32 p, %21, 0;\n"
    "wgmma.mma_async.sync.aligned.m64n32k16.f32.bf16.bf16 {%0, %1, %2, %3, %4, %5, %6, %7, %8, %9, %10, %11, %12, %13, %14, %15}, {%16,%17,%18,%19}, %20, p, 1, 1, %22;\n}\n"
    : "+f"(d[0]), "+f"(d[1]), "+f"(d[2]), "+f"(d[3]), "+f"(d[4]), "+f"(d[5]), "+f"(d[6]), "+f"(d[7]), "+f"(d[8]), "+f"(d[9]), "+f"(d[10]), "+f"(d[11]), "+f"(d[12]), "+f"(d[13]), "+f"(d[14]), "+f"(d[15])
    : "r"(a0), "r"(a1), "r"(a2), "r"(a3), "l"(db), "r"(sd), "n"(TB));
}
template<int TB> DEVI void wgmma_rs_n32z(float (&d)[16], uint32_t a0, uint32_t a1, uint32_t a2, uint32_t a3, uint64_t db){
  asm volatile("{\n.reg .pred p;\nsetp.ne.b32 p, 0, 0;\n"
    "wgmma.mma_async.sync.aligned.m64n32k16.f32.bf16.bf16 {%0, %1, %2, %3, %4, %5, %6, %7, %8, %9, %10, %11, %12, %13, %14, %15}, {%16,%17,%18,%19}, %20, p, 1, 1, %21;\n}\n"
    : "=f"(d[0]), "=f"(d[1]), "=f"(d[2]), "=f"(d[3]), "=f"(d[4]), "=f"(d[5]), "=f"(d[6]), "=f"(d[7]), "=f"(d[8]), "=f"(d[9]), "=f"(d[10]), "=f"(d[11]), "=f"(d[12]), "=f"(d[13]), "=f"(d[14]), "=f"(d[15])
    : "r"(a0), "r"(a1), "r"(a2), "r"(a3), "l"(db), "n"(TB));
}
template<int TB> DEVI void wgmma_rs_n64(float (&d)[32], uint32_t a0, uint32_t a1, uint32_t a2, uint32_t a3, uint64_t db, int sd){
  asm volatile("{\n.reg .pred p;\nsetp.ne.b32 p, %37, 0;\n"
    "wgmma.mma_async.sync.aligned.m64n64k16.f32.bf16.bf16 {%0, %1, %2, %3, %4, %5, %6, %7, %8, %9, %10, %11, %12, %13, %14, %15, %16, %17, %18, %19, %20, %21, %22, %23, %24, %25, %26, %27, %28, %29, %30, %31}, {%32,%33,%34,%35}, %36, p, 1, 1, %38;\n}\n"
    : "+f"(d[0]), "+f"(d[1]), "+f"(d[2]), "+f"(d[3]), "+f"(d[4]), "+f"(d[5]), "+f"(d[6]), "+f"(d[7]), "+f"(d[8]), "+f"(d[9]), "+f"(d[10]), "+f"(d[11]), "+f"(d[12]), "+f"(d[13]), "+f"(d[14]), "+f"(d[15]), "+f"(d[16]), "+f"(d[17]), "+f"(d[18]), "+f"(d[19]), "+f"(d[20]), "+f"(d[21]), "+f"(d[22]), "+f"(d[23]), "+f"(d[24]), "+f"(d[25]), "+f"(d[26]), "+f"(d[27]), "+f"(d[28]), "+f"(d[29]), "+f"(d[30]), "+f"(d[31])
    : "r"(a0), "r"(a1), "r"(a2), "r"(a3), "l"(db), "r"(sd), "n"(TB));
}
template<int TB> DEVI void wgmma_rs_n64z(float (&d)[32], uint32_t a0, uint32_t a1, uint32_t a2, uint32_t a3, uint64_t db){
  asm volatile("{\n.reg .pred p;\nsetp.ne.b32 p, 0, 0;\n"
    "wgmma.mma_async.sync.aligned.m64n64k16.f32.bf16.bf16 {%0, %1, %2, %3, %4, %5, %6, %7, %8, %9, %10, %11, %12, %13, %14, %15, %16, %17, %18, %19, %20, %21, %22, %23, %24, %25, %26, %27, %28, %29, %30, %31}, {%32,%33,%34,%35}, %36, p, 1, 1, %37;\n}\n"
    : "=f"(d[0]), "=f"(d[1]), "=f"(d[2]), "=f"(d[3]), "=f"(d[4]), "=f"(d[5]), "=f"(d[6]), "=f"(d[7]), "=f"(d[8]), "=f"(d[9]), "=f"(d[10]), "=f"(d[11]), "=f"(d[12]), "=f"(d[13]), "=f"(d[14]), "=f"(d[15]), "=f"(d[16]), "=f"(d[17]), "=f"(d[18]), "=f"(d[19]), "=f"(d[20]), "=f"(d[21]), "=f"(d[22]), "=f"(d[23]), "=f"(d[24]), "=f"(d[25]), "=f"(d[26]), "=f"(d[27]), "=f"(d[28]), "=f"(d[29]), "=f"(d[30]), "=f"(d[31])
    : "r"(a0), "r"(a1), "r"(a2), "r"(a3), "l"(db), "n"(TB));
}

__device__ __align__(1024) bf16 g_q[32*2048*32];
__device__ __align__(1024) bf16 g_kvb[32*16*2*128*32];
__device__ __align__(1024) bf16 g_o[2048*2048];
__device__ __align__(16) float g_kv[2*32*64*40];
__device__ __align__(1024) uint4 g_kvi[8*1280];
__device__ __align__(16) unsigned g_cnt[192];
__device__ unsigned g_tile[32*16];
__device__ unsigned g_epoch;
__device__ float g_gate[2048];
#define TS(i)
#define TR(i)
#define TC(i)
constexpr int C_KV=0, C_KI=8, C_OA=16, C_OB=32, C_G=96, C_OP=128;

constexpr float LOG2E = 1.4426950408889634f;
constexpr float SC = 0.17677669529663687f*LOG2E;
constexpr float OFFS = 88.f;
constexpr uint32_t HI64 = (512u>>4)|(2u<<30);
constexpr uint32_t HI128 = (1024u>>4)|(1u<<30);
constexpr uint32_t SB = 1024;

#define RAV 144
#define RGV 192
#define PAV 3
#define PARTV 12
#define NF 32
#define G3 1
#define W3 1
#define NPRE 2
#define GCG 1
#define GW 1
namespace k2 {
  constexpr int NST=4, GST=4;
  constexpr uint32_t SQ=SB, SKV=SQ+16384, SG=SKV+NST*16384, SW=SG+GST*32768, SONES=SW+8192, SGATE=SONES+1024, BARS=SGATE+512;
  constexpr uint32_t B_KF=BARS, B_KE=BARS+32, B_Q=BARS+64, B_W=BARS+80, B_GF=BARS+128, B_GE=BARS+192, B_PF=BARS+256, B_PE=BARS+320, B_E=BARS+96, B_X=BARS+104, SEP=BARS+384;
  constexpr uint32_t PST=49152, PR=SQ;
  constexpr uint32_t SMEM=BARS+512-SB;
  constexpr int RA=RAV, RG=RGV, RP=512-2*RAV-RGV;
  constexpr int PA=PAV, PART=PARTV;
}
struct Maps { CUtensorMap x, wa, go, woa, wob, out, wphi, wb; const bf16 *xp, *gw; };

DEVI void mnmx(const float (&p)[16], float& x0, float& x1, float& n0, float& n1){
  x0=fmaxf(p[0],p[1]); n0=fminf(p[0],p[1]); x1=fmaxf(p[2],p[3]); n1=fminf(p[2],p[3]);
  #pragma unroll
  for(int j=1;j<4;j++){ x0=fmaxf(x0,fmaxf(p[4*j],p[4*j+1])); n0=fminf(n0,fminf(p[4*j],p[4*j+1])); x1=fmaxf(x1,fmaxf(p[4*j+2],p[4*j+3])); n1=fminf(n1,fminf(p[4*j+2],p[4*j+3])); }
  #pragma unroll
  for(int o=1;o<4;o<<=1){ x0=fmaxf(x0,__shfl_xor_sync(0xffffffffu,x0,o)); x1=fmaxf(x1,__shfl_xor_sync(0xffffffffu,x1,o));
                          n0=fminf(n0,__shfl_xor_sync(0xffffffffu,n0,o)); n1=fminf(n1,__shfl_xor_sync(0xffffffffu,n1,o)); }
}

__global__ void __launch_bounds__(512,1) k_main(const __grid_constant__ Maps mp){
  using namespace k2;
  extern __shared__ __align__(1024) uint8_t smem_raw[];
  const uint32_t cb=smem_u32(smem_raw)-SB;
  if(cb&0xffffffu) asm volatile("trap;");
  const uint32_t B_KF=cb+k2::B_KF, B_KE=cb+k2::B_KE, B_Q=cb+k2::B_Q, B_W=cb+k2::B_W, B_GF=cb+k2::B_GF, B_GE=cb+k2::B_GE, SGATE=cb+k2::SGATE,
                 B_PF=cb+k2::B_PF, B_PE=cb+k2::B_PE, B_E=cb+k2::B_E, B_X=cb+k2::B_X, SEP=cb+k2::SEP;
  const int tid=threadIdx.x, lane=tid&31, warp=__shfl_sync(0xffffffffu,tid>>5,0);
  const int m=blockIdx.x&15, hh=blockIdx.x>>4;
  if(tid==0){
    for(int s=0;s<NST;s++){ mbar_init(B_KF+8*s,1); mbar_init(B_KE+8*s,8); }
    for(int s=0;s<GST;s++){ mbar_init(B_GF+8*s,1); mbar_init(B_GE+8*s,8); }
    mbar_init(B_E,1); mbar_init(B_X,1);
    mbar_init(B_Q,1); mbar_init(B_Q+8,1); mbar_init(B_W,1); mbar_init(B_W+8,1);
    asm volatile("fence.mbarrier_init.release.cluster;":::"memory"); }
  if(tid==416){
    for(int s=0;s<4;s++){ mbar_init(B_PF+8*s,1); mbar_init(B_PE+8*s,16); }
    asm volatile("fence.mbarrier_init.release.cluster;":::"memory"); fence_async_smem();
    for(int s=0;s<4;s++){ const uint32_t a=cb+PR+s*PST; mbar_expect_tx(B_PF+8*s,PST); tma2d(a,&mp.x,s*64,m*128,B_PF+8*s);
      if(s<NPRE) for(int b=0;b<4;b++) tma2d(a+16384+b*8192,&mp.wb,(b<3 ? b*1024 : 2112)+hh*128,s*64,B_PF+8*s); }
  }
  if(tid<256) asm volatile("st.shared.u32 [%0], %1;"::"r"(cb+SONES+tid*4),"r"(0x3F803F80u):"memory");
  cluster_sync();
  if(tid==0) TS(0);
  auto epoch=[&]{ mbar_wait(B_E,0); uint32_t e; asm volatile("ld.shared.u32 %0, [%1];":"=r"(e):"r"(SEP):"memory"); return e; };

  if(warp>=12){
    reg_dealloc<RP>();
    if(warp==12){
      const uint32_t tag=epoch();
      bar_sync(3,288);
      if(lane==0){
        const uint32_t pr=(m&1)^1;
        mbar_arrive_cl(mapa(B_X,pr));
        bulk_s2g(g_kvb+((size_t)(4*hh)*16+m)*8192, cb+SKV, 16384); bulk_commit();
        mbar_arrive(B_KF); mbar_expect_tx(B_KF+8,16384);
        mbar_wait(B_X,0);
        asm volatile("cp.async.bulk.shared::cluster.shared::cta.mbarrier::complete_tx::bytes [%0], [%1], %2, [%3];"::"r"(mapa(cb+SKV+16384,pr)),"r"(cb+SKV),"r"(16384),"r"(mapa(B_KF+8,pr)):"memory");
        bulk_s2g(g_kvb+((size_t)(4*hh+1)*16+m)*8192, cb+SG+3*32768, 16384);
        #pragma unroll
        for(int j=0;j<2;j++) bulk_s2g(g_kvb+((size_t)(4*hh+2+j)*16+m)*8192+4096, cb+SG+3*32768+16384+j*8192, 8192);
        bulk_commit(); bulk_wait<1>();
        flag_set_rlx(&g_tile[(4*hh)*16+m],tag); TS(18);
      }
      uint32_t ready=0;
      #pragma unroll 1
      for(int it=2;it<64;it++){ const int h=4*hh+(it>>4), t=(it+(m&14))&15, sl=it&3;
        if((it&15)==0) ready=0;
        if(!((ready>>t)&1)){
          for(int i=0;;i++){ unsigned v; asm volatile("ld.relaxed.gpu.global.u32 %0, [%1];":"=r"(v):"l"(&g_tile[h*16+(lane&15)]):"memory");
            ready=__ballot_sync(0xffffffffu, v==tag); if((ready>>t)&1) break; if(i>(1<<22)) asm volatile("trap;"); }
          asm volatile("fence.acq_rel.cta;":::"memory"); fence_async_all();
          }
        if(lane==0){
          if(it==4){ bulk_wait<0>(); flag_set_rlx(&g_tile[(4*hh+1)*16+m],tag);
            mbar_wait(B_KF+8,0); mbar_arrive_cl(mapa(B_X,(m&1)^1));
            mbar_wait(B_X,1); }
          mbar_wait(B_KE+8*sl,((it>>2)&1)^1); mbar_expect_tx(B_KF+8*sl,16384);
          bulk_g2s(cb+SKV+sl*16384, g_kvb+((size_t)h*16+t)*8192, 16384, B_KF+8*sl);
          if(it==3){ bulk_wait_read<0>();
            #pragma unroll
            for(int i=0;i<8;i++) mbar_arrive_cl(mapa(B_GE+24,i&1)); }
          if(it==16+NST || it==32+NST){ const int r=(it>>4)&1^1;
            flag_wait_eq(&g_tile[(h+1)*16+m],tag); fence_async_all();
            mbar_expect_tx(B_Q+8*r,8192); bulk_g2s(cb+SQ+r*8192, g_q+((size_t)(h+1)*2048+m*128)*32, 8192, B_Q+8*r); } }
        __syncwarp(); }
    } else if(warp==13){
      if(lane==0){
        const uint32_t rank=m&1;
        #pragma unroll 1
        for(int it=NPRE;it<16;it++){ const int s=it&3, k=it*64; const uint32_t a=cb+PR+s*PST, bar=B_PF+8*s;
          if(it>=4){ mbar_wait(B_PE+8*s,((it>>2)&1)^1); mbar_expect_tx(bar,PST); tma2d(a,&mp.x,k,m*128,bar); }
          tma2d_mc(a+16384+rank*16384,&mp.wb,rank*2048+hh*128,k,bar,3);
          tma2d_mc(a+24576+rank*16384,&mp.wb,(rank ? 2112 : 1024)+hh*128,k,bar,3); }
        mbar_expect_tx(B_W,8192); tma2d(cb+SW,&mp.wphi,0,hh*128,B_W);
        const uint32_t tag=epoch();
        #pragma unroll 1
        for(int it=0;it<93;it++){
          const int s=it&3; const uint32_t a=cb+SG+s*32768, bar=B_GF+8*s;
          mbar_wait(B_GE+8*s,(it>>2)&1);
          if(it<64){
            const int job=it>>4, k=(it&15)*64, n = job==0 ? rank*1024+hh*128+64 : job<3 ? 1024+rank*1024+hh*128+(job-1)*64 : hh*128+rank*64;
            mbar_expect_tx(bar,32768); tma2d_mc(a+16384+rank*8192,job==0 ? &mp.wb : &mp.wa,n,k,bar,3); tma2d(a,&mp.x,k,m*128,bar);
          } else if(it==64){
            flag_wait(&g_cnt[C_KI+hh],16*tag); fence_async_all();
            mbar_expect_tx(bar,20480); bulk_g2s(a,g_kvi+hh*1280,20480,bar);
          } else {
            const int j=it-65, k = j<8 ? 1024+j*64 : j<24 ? (j-8)*64 : 1024+(j-16)*64;
            mbar_expect_tx(bar,32768);
            if(k<1024) tma2d_mc(a+16384+rank*8192,&mp.woa,hh*128+rank*64,k,bar,3);
            else tma4d_mc(a+16384+rank*8192,&mp.wob,hh*128+rank*64,0,(k-1024)>>8,(k&255)>>5,bar,3);
            if(k==0){ flag_wait(&g_cnt[C_OA+m],8*tag); fence_async_all(); }
            if(k>=1024 && (k&255)==0){ flag_wait(&g_cnt[C_OB+((k-1024)>>8)*16+m],8*tag); fence_async_all(); }
            tma2d(a,&mp.go,k,m*128,bar);
          } }
        uint32_t todo=15;
        #pragma unroll 1
        for(int it=93;it<97;it++){
          const int s=it&3; const uint32_t a=cb+SG+s*32768, bar=B_GF+8*s;
          mbar_wait(B_GE+8*s,(it>>2)&1);
          uint32_t rdy=0;
          for(int i=0;!rdy;i++){ uint32_t c0,c1,c2,c3;
            asm volatile("ld.relaxed.gpu.global.v4.u32 {%0,%1,%2,%3}, [%4];":"=r"(c0),"=r"(c1),"=r"(c2),"=r"(c3):"l"(&g_cnt[C_OP+4*m]):"memory");
            rdy=todo&((c0==2*tag)|(c1==2*tag)<<1|(c2==2*tag)<<2|(c3==2*tag)<<3);
            if(i>(1<<22)) asm volatile("trap;"); }
          const int p=__ffs(rdy)-1; todo&=~(1u<<p);
          asm volatile("fence.acq_rel.cta;":::"memory"); fence_async_all();
          mbar_expect_tx(bar,32768);
          tma2d(a,&mp.go,1792+p*64,m*128,bar);
          tma4d(a+16384,&mp.wob,hh*128,0,3,2*p,bar); tma4d(a+24576,&mp.wob,hh*128+64,0,3,2*p,bar);
          if(it==96) TS(23); }
      }
    } else if(warp==14){
      const uint32_t tag=epoch();
      if(lane==0) flag_wait(&g_cnt[C_G+m],8*tag);
      __syncwarp();
      #pragma unroll
      for(int i=0;i<4;i++) asm volatile("st.shared.f32 [%0], %1;"::"r"(SGATE+(i*32+lane)*4),"f"(__ldcg(g_gate+m*128+i*32+lane)):"memory");
      __syncwarp(); if(lane==0) mbar_arrive(B_W+8);
      for(int r=0;r<4;r++){ bar_sync(2,288); if(lane==0){ flag_add(&g_cnt[r<3 ? C_OB+r*16+m : C_OP+4*m+(hh>>1)]); if(r==3) TS(22); } __syncwarp(); }
    } else {
      const uint32_t tag=ld_acq(&g_epoch)+1;
      if(lane==0){ asm volatile("st.shared.u32 [%0], %1;"::"r"(SEP),"r"(tag):"memory"); mbar_arrive(B_E); }
      #pragma unroll
      for(int i=0;i<5;i++) *(float4*)(g_kv+((tag+1)&1)*81920+blockIdx.x*640+i*128+lane*4)=make_float4(0.f,0.f,0.f,0.f);
      if(lane==0) flag_wait_eq(&g_tile[(4*hh+1)*16+m],tag);
      bar_sync(4,160);
      if(lane==0){
        #pragma unroll
        for(int j=0;j<2;j++){ bulk_s2g(g_q+((size_t)(4*hh+2+j)*2048+m*128)*32, cb+SG+3*32768+j*8192, 8192); bulk_s2g(g_kvb+((size_t)(4*hh+2+j)*16+m)*8192, cb+SG+3*32768+16384+j*8192, 8192); }
        bulk_commit(); bulk_wait_read<0>(); }
      __syncwarp();
      if(lane<8) mbar_arrive_cl(mapa(B_GE+24,lane&1));
      if(lane==0){ bulk_wait<0>(); flag_set_rlx(&g_tile[(4*hh+2)*16+m],tag); flag_set_rlx(&g_tile[(4*hh+3)*16+m],tag); }
      bar_sync(4,160);
      if(lane==0){ flag_add(&g_cnt[C_KV+hh]); flag_wait(&g_cnt[C_KV+hh],16*tag); }
      __syncwarp();
      const int f=m*16+(lane>>1), c0=(lane&1)*2; const float* src=g_kv+(tag&1)*81920+((size_t)hh*256+f)*40;
      #pragma unroll
      for(int c=c0;c<c0+2;c++){ const float4 a=__ldcg((const float4*)(src+c*8)), b=__ldcg((const float4*)(src+c*8+4));
        g_kvi[hh*1280+f*4+(c^((f>>1)&3))]=make_uint4(pack(a.x,a.y),pack(a.z,a.w),pack(b.x,b.y),pack(b.z,b.w)); }
      if((lane&1)==0) g_kvi[hh*1280+1024+(f&63)*4+((f>>6)^((f>>1)&3))]=make_uint4(pack(__ldcg(src+32),1.f),0u,0u,0u);
      __syncwarp();
      if(lane==0){ flag_add(&g_cnt[C_KI+hh]); }
      bar_sync(4,160);
      if(lane==0){ tma2d_store(&mp.go,cb+SG+3*32768,hh*128,m*128); tma2d_store(&mp.go,cb+SG+3*32768+16384,hh*128+64,m*128); bulk_commit(); bulk_wait_read<0>(); }
      __syncwarp();
      if(lane<8) mbar_arrive_cl(mapa(B_GE+24,lane&1));
      if(lane==0){ bulk_wait<0>(); flag_add_rlx(&g_cnt[C_OA+m]); }
    }
  } else if(warp>=8){
    const int wq=warp-8, t128=tid-256;
    uint32_t zz; asm volatile("mov.u32 %0, 0;":"=r"(zz)); zz=__shfl_sync(0xffffffffu,zz,0);
    int s=0; uint32_t ph=0;
    const uint32_t rel=mapa(B_GE,lane&1);
    auto release=[&](int slot){ if(lane<2) mbar_arrive_cl(rel+8*slot); };
    const int srow=wq*16+(lane&15);
    {
      #pragma unroll 1
      for(int r=0;r<4;r++){ const int row=m*128+hh*16+wq*4+r; float gs=0;
        #pragma unroll
        for(int j=0;j<4;j++){ const uint4 a=__ldg((const uint4*)(mp.xp+(size_t)row*1024+j*256+lane*8)), b=__ldg((const uint4*)(mp.gw+j*256+lane*8));
          const __nv_bfloat162* pa=(const __nv_bfloat162*)&a; const __nv_bfloat162* pb=(const __nv_bfloat162*)&b;
          #pragma unroll
          for(int e=0;e<4;e++){ float2 p=__bfloat1622float2(__hmul2(pa[e],pb[e])); gs+=p.x+p.y; } }
        #pragma unroll
        for(int o=16;o;o>>=1) gs+=__shfl_xor_sync(0xffffffffu,gs,o);
        gs=__bfloat162float(__float2bfloat16(gs));
        if(lane==0) g_gate[row]=__bfloat162float(__float2bfloat16(1.f/(1.f+__expf(-gs)))); }
      bar_sync(1,128);
      if(t128==0) flag_add(&g_cnt[C_G+m]);
      bar_sync(5,384);
      #pragma unroll
      for(int i=0;i<3;i++) release(i);
    }
    reg_alloc<RG>();
    #pragma unroll 1
    for(int job=-1;job<4;job++){
      float acc[2][64];
      auto stage=[&](const bool z, const bool rl, const int G, const int W){
        mbar_wait(B_GF+8*s,ph);
        const uint32_t ad=((SG+s*32768)>>4)|(1u<<16), bd=((SG+s*32768+16384)>>4)|((8192u>>4)<<16);
        auto wt=[&]{ wg_commit(); if(W) wg_wait<1>(); else wg_wait<0>(); };
        #pragma unroll
        for(int kk=0;kk<4;kk++){
          if(G==0 || kk%(G?G:1)==0) wg_fence();
          if(z&&kk==0) wgmma_ss_n128z<0,1>(acc[0],mk_desc2(ad,HI128),mk_desc2(bd,HI128));
          else wgmma_ss_n128<0,1>(acc[0],mk_desc2(ad+kk*2,HI128),mk_desc2(bd+kk*128,HI128),1);
          if(G==0){ wt(); if(rl && kk==0) release((s+3)&3); wg_fence(); }
          if(z&&kk==0) wgmma_ss_n128z<0,1>(acc[1],mk_desc2(ad+512,HI128),mk_desc2(bd,HI128));
          else wgmma_ss_n128<0,1>(acc[1],mk_desc2(ad+512+kk*2,HI128),mk_desc2(bd+kk*128,HI128),1);
          if(G==0 || kk%(G?G:1)==G-1){ wt(); if(rl && kk==G-1) release((s+3)&3); }
        }
        s=(s+1)&3; ph^=(s==0); };
      stage(true,false,GCG,GW);
      if(job<3){
        #pragma unroll 1
        for(int st=1;st<16;st++) stage(false,true,GCG,GW);
      } else {
        #pragma unroll 1
        for(int st=1;st<28;st++) stage(false,true,G3,W3);
        #pragma unroll 1
        for(int st=28;st<32;st++) stage(false,st==28,2,1);
      }
      wg_wait<0>();
      bar_sync(1,128);
      const uint32_t SCR = SG + (job<2 ? 3*32768 : 0);
      fence_regs(acc[0]); fence_regs(acc[1]);
      if(t128==0) TS(job<0 ? 21 : 8+2*job);
      if(job<0){
        #pragma unroll
        for(int mb=0;mb<2;mb++){ const int row=mb*64+srow;
          #pragma unroll
          for(int c=0;c<8;c++){ const float* v=&acc[mb][8*c];
            stsm4(cb+SCR+(c>>1)*8192+row*64+((((c&1)*2+(lane>>4))^((row>>1)&3))<<4), pack(v[0],v[1]),pack(v[2],v[3]),pack(v[4],v[5]),pack(v[6],v[7])); } }
        fence_async_smem(); bar_arrive(4,160);
      } else if(job<2){
        if(job==0) mbar_wait(B_W,0);
        uint32_t kf[2][16];
        #pragma unroll
        for(int mb=0;mb<2;mb++){
          #pragma unroll
          for(int i=0;i<16;i++) kf[mb][i]=pack(acc[mb][2*i],acc[mb][2*i+1]);
          const int row=mb*64+srow;
          #pragma unroll
          for(int c=0;c<4;c++){ const float* v=&acc[mb][32+8*c];
            stsm4(cb+SCR+(c>>1)*8192+row*64+((((c&1)*2+(lane>>4))^((row>>1)&3))<<4), pack(v[0],v[1]),pack(v[2],v[3]),pack(v[4],v[5]),pack(v[6],v[7])); }
        }
        float pk[2][2][16];
        wg_fence();
        #pragma unroll
        for(int h=0;h<2;h++){ const uint32_t wd=((SW+(job*2+h)*2048)>>4)|(1u<<16);
          #pragma unroll
          for(int mb=0;mb<2;mb++){
            wgmma_rs_n32z<1>(pk[h][mb],kf[mb][8*h],kf[mb][8*h+1],kf[mb][8*h+2],kf[mb][8*h+3],mk_desc2(wd,HI64));
            wgmma_rs_n32<1>(pk[h][mb],kf[mb][8*h+4],kf[mb][8*h+5],kf[mb][8*h+6],kf[mb][8*h+7],mk_desc2(wd+64,HI64),1); } }
        wg_commit(); wg_wait<0>();
        float kv[20];
        auto put_kv=[&](int h){
          wg_wait<0>(); fence_regs(kv);
          float* dst=g_kv+(epoch()&1)*81920+((size_t)(4*hh+2*job+h)*64+wq*16+(lane>>2))*40+(lane&3)*2;
          #pragma unroll
          for(int j=0;j<4;j++){ red2(dst+8*j,kv[4*j],kv[4*j+1]); red2(dst+320+8*j,kv[4*j+2],kv[4*j+3]); }
          if((lane&3)==0){ red1(dst+32,kv[16]); red1(dst+352,kv[18]); } };
        #pragma unroll
        for(int h=0;h<2;h++){
          fence_regs(pk[h][0]); fence_regs(pk[h][1]);
          uint32_t ph_[2][16];
          #pragma unroll
          for(int mb=0;mb<2;mb++){
            float (&p)[16]=pk[h][mb]; float x0,x1,n0,n1; mnmx(p,x0,x1,n0,n1);
            x0*=-LOG2E; x1*=-LOG2E; n0*=LOG2E; n1*=LOG2E;
            float ep[16],en[16],sp0=0,sp1=0,sn0=0,sn1=0;
            #pragma unroll
            for(int i=0;i<16;i++){ const bool hi=i&2; ep[i]=ex2(fmaf(p[i],LOG2E,hi?x1:x0)); en[i]=ex2(fmaf(p[i],-LOG2E,hi?n1:n0));
              if(hi){ sp1+=ep[i]; sn1+=en[i]; } else { sp0+=ep[i]; sn0+=en[i]; } }
            #pragma unroll
            for(int o=1;o<4;o<<=1){ sp0+=__shfl_xor_sync(0xffffffffu,sp0,o); sp1+=__shfl_xor_sync(0xffffffffu,sp1,o); sn0+=__shfl_xor_sync(0xffffffffu,sn0,o); sn1+=__shfl_xor_sync(0xffffffffu,sn1,o); }
            sp0=rcp(sp0); sp1=rcp(sp1); sn0=rcp(sn0); sn1=rcp(sn1);
            #pragma unroll
            for(int i=0;i<8;i++){ const bool hi=i&1; ph_[mb][i]=pack(ep[2*i]*(hi?sp1:sp0),ep[2*i+1]*(hi?sp1:sp0)); ph_[mb][8+i]=pack(en[2*i]*(hi?sn1:sn0),en[2*i+1]*(hi?sn1:sn0)); }
          }
          if(h==1){
            #pragma unroll
            for(int i=0;i<16;i++) asm volatile(""::"r"(ph_[0][i]),"r"(ph_[1][i]));
            put_kv(0); bar_sync(1,128); }
          #pragma unroll
          for(int mb=0;mb<2;mb++){ const int row=mb*64+srow;
            #pragma unroll
            for(int c=0;c<4;c++) stsm4(cb+SCR+16384+row*128+(((2*c+(lane>>4))^(row&7))<<4), ph_[mb][4*c],ph_[mb][4*c+1],ph_[mb][4*c+2],ph_[mb][4*c+3]); }
          fence_async_smem(); bar_sync(1,128);
          const uint32_t pd=((SCR+16384)>>4)|(1u<<16), vd=((SCR+h*8192)>>4)|(((SONES-SCR-h*8192)>>4)<<16);
          wg_fence();
          wgmma_ss_n40z<1,1>(kv,mk_desc2(pd,HI128),mk_desc2(vd,HI64));
          #pragma unroll
          for(int ks=1;ks<8;ks++) wgmma_ss_n40<1,1>(kv,mk_desc2(pd+ks*128,HI128),mk_desc2(vd+ks*(64u-(64u<<16)),HI64),1);
          wg_commit();
        }
        put_kv(1);
        release(3);
        if(job==1) bar_arrive(4,160);
      } else if(job==2){
        uint32_t qf[2][32];
        #pragma unroll
        for(int mb=0;mb<2;mb++){
          #pragma unroll
          for(int i=0;i<32;i++) qf[mb][i]=pack(acc[mb][2*i],acc[mb][2*i+1]); }
        float pq[2][16], op[20], on[20]; uint32_t e[2][16];
        auto PQ=[&](const int i){ const int h=i>>1, mb=i&1; const uint32_t wd=((SW+h*2048)>>4)|(1u<<16);
          wgmma_rs_n32z<1>(pq[mb],qf[mb][8*h],qf[mb][8*h+1],qf[mb][8*h+2],qf[mb][8*h+3],mk_desc2(wd,HI64));
          wgmma_rs_n32<1>(pq[mb],qf[mb][8*h+4],qf[mb][8*h+5],qf[mb][8*h+6],qf[mb][8*h+7],mk_desc2(wd+64,HI64),1); };
        auto EX=[&](const int b){
          float (&p)[16]=pq[b]; fence_regs(p); float x0,x1,n0,n1; mnmx(p,x0,x1,n0,n1);
          x0*=-LOG2E; x1*=-LOG2E; n0*=LOG2E; n1*=LOG2E;
          #pragma unroll
          for(int i=0;i<8;i++){ const bool hi=i&1;
            e[b][i]=pack(ex2(fmaf(p[2*i],LOG2E,hi?x1:x0)),ex2(fmaf(p[2*i+1],LOG2E,hi?x1:x0)));
            e[b][8+i]=pack(ex2(fmaf(p[2*i],-LOG2E,hi?n1:n0)),ex2(fmaf(p[2*i+1],-LOG2E,hi?n1:n0))); }
          #pragma unroll
          for(int i=0;i<16;i++) asm volatile(""::"r"(e[b][i])); };
        wg_fence(); PQ(0); PQ(1); wg_commit(); wg_wait<0>();
        EX(0);
        mbar_wait(B_GF,ph); mbar_wait(B_W+8,0);
        float gt[4];
        #pragma unroll
        for(int i=0;i<4;i++) asm volatile("ld.shared.f32 %0, [%1];":"=f"(gt[i]):"r"(SGATE+((i>>1)*64+(i&1)*8+wq*16+(lane>>2))*4));
        #pragma unroll
        for(int i=0;i<8;i++){ const int h=i>>1, mb=i&1;
          const uint32_t kd=((SCR+h*4096)>>4)|(((16384+16*h-h*4096)>>4)<<16);
          wg_fence();
          wgmma_rs_n40z<1>(op,e[mb][0],e[mb][1],e[mb][2],e[mb][3],mk_desc2(kd,HI64));
          wgmma_rs_n40<1>(op,e[mb][4],e[mb][5],e[mb][6],e[mb][7],mk_desc2(kd+64,HI64),1);
          wgmma_rs_n40z<1>(on,e[mb][8],e[mb][9],e[mb][10],e[mb][11],mk_desc2(kd+128,HI64));
          wgmma_rs_n40<1>(on,e[mb][12],e[mb][13],e[mb][14],e[mb][15],mk_desc2(kd+192,HI64),1);
          if(i<6) PQ(i+2);
          wg_commit();
          if(i<7) EX(mb^1);
          BOUND(40+i);
          wg_wait<0>(); fence_regs(op); fence_regs(on);
          float a0=rcp(op[17]), b0=rcp(on[17]), a1=rcp(op[19]), b1=rcp(on[19]);
          const float f0=__fdividef(gt[2*mb],op[16]*a0+on[16]*b0+1e-6f), f1=__fdividef(gt[2*mb+1],op[18]*a1+on[18]*b1+1e-6f);
          a0=__shfl_sync(0xffffffffu,a0*f0,lane&28); b0=__shfl_sync(0xffffffffu,b0*f0,lane&28);
          a1=__shfl_sync(0xffffffffu,a1*f1,lane&28); b1=__shfl_sync(0xffffffffu,b1*f1,lane&28);
          const int row=mb*64+srow;
          #pragma unroll
          for(int c=0;c<2;c++){ const float* p=&op[8*c]; const float* n=&on[8*c];
            stsm4(cb+SG+3*32768+(h>>1)*16384+row*128+((((h&1)*4+c*2+(lane>>4))^(row&7))<<4),
                  pack(p[0]*a0+n[0]*b0,p[1]*a0+n[1]*b0),pack(p[2]*a1+n[2]*b1,p[3]*a1+n[3]*b1),pack(p[4]*a0+n[4]*b0,p[5]*a0+n[5]*b0),pack(p[6]*a1+n[6]*b1,p[7]*a1+n[7]*b1)); }
        }
        fence_async_smem();
        release(0); s=1;
        bar_arrive(4,160);
      } else {
        #pragma unroll
        for(int mb=0;mb<2;mb++){ const int row=mb*64+srow;
          #pragma unroll
          for(int c=0;c<8;c++){ const float* v=&acc[mb][8*c];
            stsm4(cb+SCR+(c>>2)*16384+row*128+((((c&3)*2+(lane>>4))^(row&7))<<4), pack(v[0],v[1]),pack(v[2],v[3]),pack(v[4],v[5]),pack(v[6],v[7])); } }
        fence_async_smem(); bar_sync(1,128);
        if(t128==0){ tma2d_store(&mp.out,cb+SCR,hh*128,m*128); tma2d_store(&mp.out,cb+SCR+16384,hh*128+64,m*128); bulk_commit();
          if(blockIdx.x==0) g_epoch=epoch();
          bulk_wait_read<0>(); }
      }
      if(t128==0) TS(job<0 ? 17 : 9+2*job);
    }
  } else {
    reg_alloc<168>();
    constexpr uint32_t kd0=(SKV>>4)|(1u<<16), vd0=((SKV+8192)>>4)|(((SONES-SKV-8192)>>4)<<16);
    {
      const uint32_t prel=mapa(B_PE,lane&1); const int row=warp*16+(lane&15);
      const uint32_t so=cb+row*64, sx=(row>>1)&3;
      float acc[2][64];
      auto pa=[&](const int k, const bool z){
        const int ps=k&3;
        mbar_wait(B_PF+8*ps,(k>>2)&1);
        if(z && tid==0){ TS(1); TC(19); }
        const uint32_t ad=((PR+ps*PST+(warp>>2)*8192)>>4)|(1u<<16), bd=((PR+ps*PST+16384)>>4)|((8192u>>4)<<16);
        wg_fence();
        #pragma unroll
        for(int kk=0;kk<4;kk++){
          #pragma unroll
          for(int nb=0;nb<2;nb++){
            if(z&&kk==0) wgmma_ss_n128z<0,1>(acc[nb],mk_desc2(ad,HI128),mk_desc2(bd+nb*1024,HI128));
            else wgmma_ss_n128<0,1>(acc[nb],mk_desc2(ad+kk*2,HI128),mk_desc2(bd+nb*1024+kk*128,HI128),1); }
          if(kk==0){ wg_commit(); wg_wait<1>(); if(!z && k<13 && lane<2) mbar_arrive_cl(prel+8*((k+3)&3)); wg_fence(); } }
        wg_commit(); };
      pa(0,true);
      #pragma unroll 1
      for(int k=1;k<16;k++) pa(k,false);
      wg_wait<0>(); fence_regs(acc[0]); fence_regs(acc[1]);
      bar_sync(5,384);
      if(tid==0){ TS(2); TC(20); }
      #pragma unroll
      for(int c=0;c<16;c++){ const float* v=&acc[c>>3][8*(c&7)]; const int j=(c>>1)&1, bx=c>>2;
        stsm4(so+(bx==0 ? SQ+j*8192 : bx<3 ? (j ? SG+3*32768 : SKV)+(bx-1)*8192 : SG+3*32768+16384+j*8192)+((((c&1)*2+(lane>>4))^sx)<<4), pack(v[0],v[1]),pack(v[2],v[3]),pack(v[4],v[5]),pack(v[6],v[7])); }
      fence_async_smem(); bar_sync(3,288);
    }
    reg_dealloc<RA>();
    float o[20], S0[32], S1[32], nb0=0, nb1=0; uint32_t P0[16], P1[16];
    #pragma unroll
    for(int i=0;i<20;i++) o[i]=0;
    #pragma unroll
    for(int i=0;i<16;i++) P1[i]=0;
    fence_regs(o);
    uint32_t qf[8];
    auto ldq=[&](int u){ uint32_t t; asm volatile("mov.u32 %0, %%tid.x;":"=r"(t));
      const uint32_t row=(t>>5)*16+(t&15), a=cb+SQ+(u&1)*8192+row*64;
      #pragma unroll
      for(int kk=0;kk<2;kk++) asm volatile("ldmatrix.sync.aligned.m8n8.x4.shared.b16 {%0,%1,%2,%3}, [%4];":"=r"(qf[4*kk]),"=r"(qf[4*kk+1]),"=r"(qf[4*kk+2]),"=r"(qf[4*kk+3])
        :"r"(a+(((2*kk+((t>>4)&1))^((row>>1)&3))<<4)):"memory"); };
    ldq(0);
    auto qk=[&](float (&S)[32], uint32_t kd){
      wgmma_rs_n64z<0>(S,qf[0],qf[1],qf[2],qf[3],mk_desc2(kd,HI64));
      wgmma_rs_n64<0>(S,qf[4],qf[5],qf[6],qf[7],mk_desc2(kd+2,HI64),1); };
    if(tid==0) TS(3);
    wg_fence(); qk(S0,kd0); wg_commit(); wg_wait<0>(); fence_regs(S0);
    auto epi=[&](int r){
      uint32_t cta,t; asm volatile("mov.u32 %0, %%ctaid.x;":"=r"(cta)); asm volatile("mov.u32 %0, %%tid.x;":"=r"(t));
      const int lr=(t>>5)*16+((t&31)>>2), head=4*(cta>>4)+r, ocol=1024+r*256+(cta>>4)*32;
      if(r==0) mbar_wait(B_W+8,0);
      float g0,g1; asm volatile("ld.shared.f32 %0, [%1];":"=f"(g0):"r"(SGATE+lr*4)); asm volatile("ld.shared.f32 %0, [%1];":"=f"(g1):"r"(SGATE+lr*4+32));
      g0=__bfloat162float(__float2bfloat16(1.f-g0)); g1=__bfloat162float(__float2bfloat16(1.f-g1));
      const float f0=__fdividef(g0,o[16]), f1=__fdividef(g1,o[18]);
      bf16* orow=g_o+(size_t)((cta&15)*128+lr)*2048+ocol;
      uint32_t* d=(uint32_t*)(orow+(t&3)*2);
      float t0=0,t1=0;
      #pragma unroll
      for(int j=0;j<4;j++){ d[4*j]=pack(o[4*j]*f0,o[4*j+1]*f0); d[8192+4*j]=pack(o[4*j+2]*f1,o[4*j+3]*f1);
        t0+=fabsf(o[4*j])+fabsf(o[4*j+1]); t1+=fabsf(o[4*j+2])+fabsf(o[4*j+3]); }
      const unsigned b0=__ballot_sync(0xffffffffu,!(o[16]<1e30f && t0<3e38f)), b1=__ballot_sync(0xffffffffu,!(o[18]<1e30f && t1<3e38f));
      if(b0|b1){
        const int ln=t&31; const uint8_t* kv=(const uint8_t*)(g_kvb+(size_t)head*16*8192);
        #pragma unroll 1
        for(int rr=0;rr<16;rr++){
          if(!(((rr<8?b0:b1)>>((rr&7)*4))&15)) continue;
          const int qrow=(t>>5)*16+rr; const uint32_t qa=cb+SQ+(r&1)*8192+qrow*64;
          auto dot=[&](int key){ float s=0; const uint8_t* kr=kv+(key>>7)*16384+(key&127)*64;
            #pragma unroll 1
            for(int c=0;c<4;c++){ uint4 a=__ldcg((const uint4*)(kr+((c^((key>>1)&3))<<4))), b;
              asm volatile("ld.shared.v4.u32 {%0,%1,%2,%3}, [%4];":"=r"(b.x),"=r"(b.y),"=r"(b.z),"=r"(b.w):"r"(qa+((c^((qrow>>1)&3))<<4)));
              const uint32_t* pa=&a.x; const uint32_t* pb=&b.x;
              #pragma unroll
              for(int e=0;e<4;e++){ s=fmaf(__uint_as_float(pa[e]<<16),__uint_as_float(pb[e]<<16),s); s=fmaf(__uint_as_float(pa[e]&0xffff0000u),__uint_as_float(pb[e]&0xffff0000u),s); } }
            return s; };
          float mx=-INFINITY;
          #pragma unroll 1
          for(int k=ln;k<2048;k+=32) mx=fmaxf(mx,dot(k));
          #pragma unroll
          for(int of=16;of;of>>=1) mx=fmaxf(mx,__shfl_xor_sync(0xffffffffu,mx,of));
          float a=0,l=0;
          #pragma unroll 1
          for(int k0=0;k0<2048;k0+=32){ const float p=ex2((dot(k0+ln)-mx)*SC); l+=p;
            #pragma unroll 1
            for(int j=0;j<32;j++){ const int key=k0+j; const unsigned short vv=__ldcg((const unsigned short*)(kv+(key>>7)*16384+8192+(key&127)*64+(((ln>>3)^((key>>1)&3))<<4)+(ln&7)*2));
              a=fmaf(__shfl_sync(0xffffffffu,p,j),__uint_as_float((uint32_t)vv<<16),a); } }
          #pragma unroll
          for(int of=16;of;of>>=1) l+=__shfl_xor_sync(0xffffffffu,l,of);
          float g; asm volatile("ld.shared.f32 %0, [%1];":"=f"(g):"r"(SGATE+qrow*4));
          g=__bfloat162float(__float2bfloat16(1.f-g));
          __syncwarp();
          g_o[(size_t)((cta&15)*128+qrow)*2048+ocol+ln]=__float2bfloat16(a*g/l);
        }
      }
      bar_arrive(2,288);
      if(t==0){ TS(4+r); if(r==3) TC(16); }
    };
    const bool l0 = lane==0;
    uint32_t zz; asm volatile("mov.u32 %0, 0;":"=r"(zz)); zz=__shfl_sync(0xffffffffu,zz,0);
    uint32_t sp=NST-1, sc=0, sn=1, phn=0;
    auto newmax=[&](float (&S)[32]){
      float m0=S[0],m1=S[2];
      #pragma unroll
      for(int i=0;i<8;i++){ m0=fmaxf(m0,fmaxf(S[4*i],S[4*i+1])); m1=fmaxf(m1,fmaxf(S[4*i+2],S[4*i+3])); }
      m0=fmaxf(m0,__shfl_xor_sync(0xffffffffu,m0,1)); m0=fmaxf(m0,__shfl_xor_sync(0xffffffffu,m0,2));
      m1=fmaxf(m1,__shfl_xor_sync(0xffffffffu,m1,1)); m1=fmaxf(m1,__shfl_xor_sync(0xffffffffu,m1,2));
      nb0=-(m0*SC+OFFS); nb1=-(m1*SC+OFFS); };
    newmax(S0);
    #pragma unroll
    for(int i=0;i<NF;i++) S0[i]=fmaf(S0[i],SC,((i>>1)&1)?nb1:nb0);
    auto step=[&](const int r, const int MODE, const int U, float (&S)[32], uint32_t (&P)[16], float (&Sn)[32], uint32_t (&Pp)[16]){
      const bool first=(U==0)&&MODE==1, second=(U==1)&&MODE==1, last=(U==1)&&MODE==2;
      if(second && r>0) epi(r-1);
      if(last){ if(r==1 || r==2) mbar_wait(B_Q+8*((r+1)&1),0); ldq(r+1); }
      const uint32_t vd= U==0 ? vd0+sp*(1024u-(1024u<<16))+4*(64u-(64u<<16)) : vd0+sc*(1024u-(1024u<<16));
      const uint32_t kd= U==0 ? kd0+sc*1024u+256u : kd0+sn*1024u;
      bool ok=true;
      const float c0=nb0, c1=nb1;
      auto ex=[&](const int i){ if(2*i>=NF) P[i]=pack(ex2(fmaf(S[2*i],SC,(i&1)?c1:c0)),ex2(fmaf(S[2*i+1],SC,(i&1)?c1:c0))); else P[i]=pack(ex2(S[2*i]),ex2(S[2*i+1])); };
      if(U==0 && !(MODE==2 && r==3)) ok=mbar_try(B_KF+8*sn, phn);
      wg_fence();
      qk(Sn,kd); wg_commit();
      #pragma unroll
      for(int kk=0;kk<4;kk++){
        if(second&&kk==0) wgmma_rs_n40z<1>(o,Pp[4*kk],Pp[4*kk+1],Pp[4*kk+2],Pp[4*kk+3],mk_desc2(vd+kk*(64u-(64u<<16)),HI64));
        else wgmma_rs_n40<1>(o,Pp[4*kk],Pp[4*kk+1],Pp[4*kk+2],Pp[4*kk+3],mk_desc2(vd+kk*(64u-(64u<<16)),HI64),1); }
      wg_commit();
      #pragma unroll
      for(int i=0;i<PA;i++) ex(i);
      #pragma unroll
      for(int i=0;i<PA;i++) asm volatile(""::"r"(P[i]));
      if(U==0){ if(__builtin_expect(!ok,0)) mbar_wait(B_KF+8*sn, phn); } else BOUND(1+MODE*8);
      #pragma unroll
      for(int i=PA;i<PART;i++) ex(i);
      #pragma unroll
      for(int i=PA;i<PART;i++) asm volatile(""::"r"(P[i]));
      BOUND(2+U+MODE*8);
      wg_wait<1>(); fence_regs(Sn);
      if(last) newmax(Sn);
      #pragma unroll
      for(int j=0;j<32;j++){
        if((j+1)*NF/32 != j*NF/32){ const int q=j*NF/32; Sn[q]=fmaf(Sn[q],SC,((q>>1)&1)?nb1:nb0); }
        if((j+1)*(16-PART)/32 != j*(16-PART)/32) ex(PART+j*(16-PART)/32); }
      fence_regs(Sn);
      #pragma unroll
      for(int i=PART;i<16;i++) asm volatile(""::"r"(P[i]));
      wg_wait<0>(); fence_regs(o);
      if(U==0){ if(l0 && !(first && r==0)) mbar_arrive(B_KE+8*sp);
      }
      else { sp=sc; sc=sn; sn=sn+1==NST?0:sn+1; phn^=(sn==0); }
    };
    #pragma unroll 1
    for(int r=0;r<4;r++){
      step(r,1,0,S0,P0,S1,P1); step(r,1,1,S1,P1,S0,P0);
      #pragma unroll 1
      for(int t=0;t<14;t++){ step(r,0,0,S0,P0,S1,P1); step(r,0,1,S1,P1,S0,P0); }
      step(r,2,0,S0,P0,S1,P1); step(r,2,1,S1,P1,S0,P0);
    }
    { const uint32_t vd=vd0+sp*(1024u-(1024u<<16))+4*(64u-(64u<<16));
      wg_fence();
      #pragma unroll
      for(int kk=0;kk<4;kk++) wgmma_rs_n40<1>(o,P1[4*kk],P1[4*kk+1],P1[4*kk+2],P1[4*kk+3],mk_desc2(vd+kk*(64u-(64u<<16)),HI64),1);
      wg_commit(); }
    wg_wait<0>(); fence_regs(o);
    epi(3);
  }
}

typedef CUresult (*PFN_enc)(CUtensorMap*, CUtensorMapDataType, cuuint32_t, void*, const cuuint64_t*, const cuuint64_t*, const cuuint32_t*, const cuuint32_t*, CUtensorMapInterleave, CUtensorMapSwizzle, CUtensorMapL2promotion, CUtensorMapFloatOOBfill);
static CUtensorMap mk_map(PFN_enc fn, const void* p, int rank, const cuuint64_t* dims, const cuuint64_t* strides, const cuuint32_t* box, CUtensorMapSwizzle sw){
  CUtensorMap m; cuuint32_t es[4]={1,1,1,1};
  fn(&m, CU_TENSOR_MAP_DATA_TYPE_BFLOAT16, rank, (void*)p, dims, strides, box, es, CU_TENSOR_MAP_INTERLEAVE_NONE, sw, CU_TENSOR_MAP_L2_PROMOTION_L2_256B, CU_TENSOR_MAP_FLOAT_OOB_FILL_NONE);
  return m; }
static CUtensorMap map2d(PFN_enc fn, const void* p, uint64_t inner, uint64_t outer, uint32_t bi, uint32_t bo, CUtensorMapSwizzle sw){
  cuuint64_t d[2]={inner,outer}, s[1]={inner*2}; cuuint32_t b[2]={bi,bo}; return mk_map(fn,p,2,d,s,b,sw); }

extern "C" void kernel_launch(void* const* d_in, const int* in_sizes, int n_in, void* d_out, int out_size){
  static bool init=false; static Maps mp; static const void* key[8];
  const void* cur[8]={d_in[0],d_in[1],d_in[2],d_in[3],d_in[5],d_in[6],d_in[7],d_out};
  bool same=init; for(int i=0;i<8;i++) same = same && key[i]==cur[i];
  if(!same){
    PFN_enc fn=nullptr; cudaDriverEntryPointQueryResult q; cudaGetDriverEntryPoint("cuTensorMapEncodeTiled",(void**)&fn,cudaEnableDefault,&q);
    void* go; cudaGetSymbolAddress(&go,g_o);
    const CUtensorMapSwizzle S128=CU_TENSOR_MAP_SWIZZLE_128B;
    mp.x=map2d(fn,d_in[0],1024,2048,64,128,S128);
    mp.wa=map2d(fn,d_in[1],3072,1024,64,64,S128);
    mp.wb=map2d(fn,d_in[5],3072,1024,64,64,S128);
    mp.go=map2d(fn,go,2048,2048,64,128,S128);
    mp.woa=map2d(fn,d_in[3],1024,1024,64,64,S128);
    { cuuint64_t d[4]={1024,32,4,8}, s[3]={2048,65536,262144}; cuuint32_t b[4]={64,32,1,2}; mp.wob=mk_map(fn,d_in[6],4,d,s,b,S128); }
    mp.out=map2d(fn,d_out,1024,2048,64,128,S128);
    mp.wphi=map2d(fn,d_in[2],32,1024,32,128,CU_TENSOR_MAP_SWIZZLE_64B);
    mp.xp=(const bf16*)d_in[0]; mp.gw=(const bf16*)d_in[7];
    cudaFuncSetAttribute(k_main,cudaFuncAttributeMaxDynamicSharedMemorySize,k2::SMEM);
    for(int i=0;i<8;i++) key[i]=cur[i];
    init=true;
  }
  cudaLaunchConfig_t cfg={}; cfg.gridDim=128; cfg.blockDim=512; cfg.dynamicSmemBytes=k2::SMEM; cfg.stream=cudaStreamPerThread;
  cudaLaunchAttribute at[1];
  at[0].id=cudaLaunchAttributeClusterDimension; at[0].val.clusterDim.x=2; at[0].val.clusterDim.y=1; at[0].val.clusterDim.z=1;
  cfg.attrs=at; cfg.numAttrs=1;
  cudaLaunchKernelEx(&cfg,k_main,mp);
}
```

```cpp
#include <cuda_runtime.h>
#include <cuda_bf16.h>
#include <cuda.h>
#include <stdint.h>

typedef __nv_bfloat16 bf16;
#define DEVI __device__ __forceinline__

DEVI uint32_t smem_u32(const void* p){ return (uint32_t)__cvta_generic_to_shared(p); }
DEVI void mbar_init(uint32_t bar, uint32_t cnt){ asm volatile("mbarrier.init.shared::cta.b64 [%0], %1;"::"r"(bar),"r"(cnt):"memory"); }
DEVI void mbar_expect_tx(uint32_t bar, uint32_t bytes){ asm volatile("mbarrier.arrive.expect_tx.shared::cta.b64 _, [%0], %1;"::"r"(bar),"r"(bytes):"memory"); }
DEVI void mbar_arrive(uint32_t bar){ asm volatile("mbarrier.arrive.shared::cta.b64 _, [%0];"::"r"(bar):"memory"); }
DEVI bool mbar_try(uint32_t bar, uint32_t parity){ uint32_t ok;
  asm volatile("{\n.reg .pred p;\nmbarrier.try_wait.parity.shared::cta.b64 p, [%1], %2;\nselp.u32 %0, 1, 0, p;\n}\n":"=r"(ok):"r"(bar),"r"(parity):"memory"); return ok; }
DEVI void mbar_wait(uint32_t bar, uint32_t parity){
  asm volatile("{\n.reg .pred p;\n.reg .u32 c;\nmov.u32 c, 0;\nLAB_WAIT:\nmbarrier.try_wait.parity.shared::cta.b64 p, [%0], %1;\n@p bra DONE;\nadd.u32 c, c, 1;\nsetp.lt.u32 p, c, 0x200000;\n@p bra LAB_WAIT;\ntrap;\nDONE:\n}\n"::"r"(bar),"r"(parity):"memory"); }
DEVI void tma2d(uint32_t dst, const CUtensorMap* m, int c0, int c1, uint32_t bar){
  asm volatile("cp.async.bulk.tensor.2d.shared::cluster.global.mbarrier::complete_tx::bytes [%0], [%1, {%3, %4}], [%2];"::"r"(dst),"l"(m),"r"(bar),"r"(c0),"r"(c1):"memory"); }
DEVI void tma2d_mc(uint32_t dst, const CUtensorMap* m, int c0, int c1, uint32_t bar, uint16_t mask){
  asm volatile("cp.async.bulk.tensor.2d.shared::cluster.global.mbarrier::complete_tx::bytes.multicast::cluster [%0], [%1, {%3, %4}], [%2], %5;"::"r"(dst),"l"(m),"r"(bar),"r"(c0),"r"(c1),"h"(mask):"memory"); }
DEVI void tma3d_mc(uint32_t dst, const CUtensorMap* m, int c0, int c1, int c2, uint32_t bar, uint16_t mask){
  asm volatile("cp.async.bulk.tensor.3d.shared::cluster.global.mbarrier::complete_tx::bytes.multicast::cluster [%0], [%1, {%3, %4, %5}], [%2], %6;"::"r"(dst),"l"(m),"r"(bar),"r"(c0),"r"(c1),"r"(c2),"h"(mask):"memory"); }
DEVI void tma4d_mc(uint32_t dst, const CUtensorMap* m, int c0, int c1, int c2, int c3, uint32_t bar, uint16_t mask){
  asm volatile("cp.async.bulk.tensor.4d.shared::cluster.global.mbarrier::complete_tx::bytes.multicast::cluster [%0], [%1, {%3, %4, %5, %6}], [%2], %7;"::"r"(dst),"l"(m),"r"(bar),"r"(c0),"r"(c1),"r"(c2),"r"(c3),"h"(mask):"memory"); }
DEVI void tma4d(uint32_t dst, const CUtensorMap* m, int c0, int c1, int c2, int c3, uint32_t bar){
  asm volatile("cp.async.bulk.tensor.4d.shared::cluster.global.mbarrier::complete_tx::bytes [%0], [%1, {%3, %4, %5, %6}], [%2];"::"r"(dst),"l"(m),"r"(bar),"r"(c0),"r"(c1),"r"(c2),"r"(c3):"memory"); }
DEVI uint32_t mapa(uint32_t a, uint32_t rank){ uint32_t r; asm("mapa.shared::cluster.u32 %0, %1, %2;":"=r"(r):"r"(a),"r"(rank)); return r; }
DEVI void mbar_arrive_cl(uint32_t a){ asm volatile("mbarrier.arrive.shared::cluster.b64 _, [%0];"::"r"(a):"memory"); }
DEVI void cluster_sync(){ asm volatile("barrier.cluster.arrive.relaxed.aligned;\nbarrier.cluster.wait.acquire.aligned;":::"memory"); }
DEVI void tma3d(uint32_t dst, const CUtensorMap* m, int c0, int c1, int c2, uint32_t bar){
  asm volatile("cp.async.bulk.tensor.3d.shared::cluster.global.mbarrier::complete_tx::bytes [%0], [%1, {%3, %4, %5}], [%2];"::"r"(dst),"l"(m),"r"(bar),"r"(c0),"r"(c1),"r"(c2):"memory"); }
DEVI void tma2d_store(const CUtensorMap* m, uint32_t src, int c0, int c1){
  asm volatile("cp.async.bulk.tensor.2d.global.shared::cta.bulk_group [%0, {%2, %3}], [%1];"::"l"(m),"r"(src),"r"(c0),"r"(c1):"memory"); }
DEVI void bulk_g2s(uint32_t dst, const void* src, uint32_t bytes, uint32_t bar){
  asm volatile("cp.async.bulk.shared::cluster.global.mbarrier::complete_tx::bytes [%0], [%1], %2, [%3];"::"r"(dst),"l"(src),"r"(bytes),"r"(bar):"memory"); }
DEVI void bulk_s2g(void* dst, uint32_t src, uint32_t bytes){
  asm volatile("cp.async.bulk.global.shared::cta.bulk_group [%0], [%1], %2;"::"l"(dst),"r"(src),"r"(bytes):"memory"); }
DEVI void bulk_commit(){ asm volatile("cp.async.bulk.commit_group;":::"memory"); }
template<int N> DEVI void bulk_wait(){ asm volatile("cp.async.bulk.wait_group %0;"::"n"(N):"memory"); }
template<int N> DEVI void bulk_wait_read(){ asm volatile("cp.async.bulk.wait_group.read %0;"::"n"(N):"memory"); }
DEVI void fence_async_smem(){ asm volatile("fence.proxy.async.shared::cta;":::"memory"); }
DEVI void fence_async_all(){ asm volatile("fence.proxy.async.global;":::"memory"); }
DEVI void wg_fence(){ asm volatile("wgmma.fence.sync.aligned;":::"memory"); }
DEVI void wg_commit(){ asm volatile("wgmma.commit_group.sync.aligned;":::"memory"); }
template<int N> DEVI void wg_wait(){ asm volatile("wgmma.wait_group.sync.aligned %0;"::"n"(N):"memory"); }
DEVI uint64_t mk_desc2(uint32_t lo, uint32_t hi){ uint64_t d; asm("mov.b64 %0, {%1,%2};":"=l"(d):"r"(lo),"r"(hi)); return d; }
template<int R> DEVI void reg_alloc(){ asm volatile("setmaxnreg.inc.sync.aligned.u32 %0;"::"n"(R)); }
template<int R> DEVI void reg_dealloc(){ asm volatile("setmaxnreg.dec.sync.aligned.u32 %0;"::"n"(R)); }
template<int N> DEVI void fence_regs(float (&r)[N]){
  #pragma unroll
  for(int i=0;i<N;i++) asm volatile("":"+f"(r[i])::"memory"); }
DEVI void griddep_wait(){ asm volatile("griddepcontrol.wait;":::"memory"); }
DEVI void bar_sync(int id, int n){ asm volatile("bar.sync %0, %1;"::"r"(id),"r"(n):"memory"); }
DEVI void bar_arrive(int id, int n){ asm volatile("bar.arrive %0, %1;"::"r"(id),"r"(n):"memory"); }
DEVI float ex2(float x){ float y; asm("ex2.approx.ftz.f32 %0,%1;":"=f"(y):"f"(x)); return y; }
DEVI float rcp(float x){ float y; asm("rcp.approx.ftz.f32 %0,%1;":"=f"(y):"f"(x)); return y; }
DEVI uint32_t pack(float lo,float hi){ uint32_t y; asm("cvt.rn.bf16x2.f32 %0,%1,%2;":"=r"(y):"f"(hi),"f"(lo)); return y; }
DEVI void stsm4(uint32_t a, uint32_t r0, uint32_t r1, uint32_t r2, uint32_t r3){
  asm volatile("stmatrix.sync.aligned.m8n8.x4.shared.b16 [%0], {%1,%2,%3,%4};"::"r"(a),"r"(r0),"r"(r1),"r"(r2),"r"(r3):"memory"); }
DEVI void flag_add(unsigned* p){ asm volatile("fence.acq_rel.gpu;\nred.relaxed.gpu.global.add.u32 [%0], 1;"::"l"(p):"memory"); }
DEVI unsigned ld_acq(const unsigned* p){ unsigned v; asm volatile("ld.acquire.gpu.global.u32 %0, [%1];":"=r"(v):"l"(p):"memory"); return v; }
DEVI void flag_set(unsigned* p, unsigned v){ asm volatile("st.release.gpu.global.u32 [%0], %1;"::"l"(p),"r"(v):"memory"); }
DEVI void flag_set_rlx(unsigned* p, unsigned v){ asm volatile("fence.proxy.async.global;\nst.relaxed.gpu.global.u32 [%0], %1;"::"l"(p),"r"(v):"memory"); }
DEVI void flag_add_rlx(unsigned* p){ asm volatile("fence.proxy.async.global;\nred.relaxed.gpu.global.add.u32 [%0], 1;"::"l"(p):"memory"); }
DEVI void flag_wait(const unsigned* p, unsigned target){
  for(int i=0;i<(1<<22);i++){ if((int)(ld_acq(p)-target)>=0) return; __nanosleep(40); }
  asm volatile("trap;"); }
DEVI void flag_wait_eq(const unsigned* p, unsigned tag){
  for(int i=0;i<(1<<22);i++){ if(ld_acq(p)==tag) return; __nanosleep(40); }
  asm volatile("trap;"); }
DEVI void red2(float* p, float a, float b){ asm volatile("red.relaxed.gpu.global.add.v2.f32 [%0], {%1,%2};"::"l"(p),"f"(a),"f"(b):"memory"); }
DEVI void red1(float* p, float a){ asm volatile("red.relaxed.gpu.global.add.f32 [%0], %1;"::"l"(p),"f"(a):"memory"); }
#define BOUND(c) asm volatile("{\n.reg .pred p;\nsetp.eq.u32 p, %0, %1;\n@p exit;\n}\n"::"r"(zz),"r"(c):"memory")
template<int TB> DEVI void wgmma_rs_n128(float (&d)[64], uint32_t a0, uint32_t a1, uint32_t a2, uint32_t a3, uint64_t db, int sd){
  asm volatile("{\n.reg .pred p;\nsetp.ne.b32 p, %69, 0;\n"
    "wgmma.mma_async.sync.aligned.m64n128k16.f32.bf16.bf16 {%0, %1, %2, %3, %4, %5, %6, %7, %8, %9, %10, %11, %12, %13, %14, %15, %16, %17, %18, %19, %20, %21, %22, %23, %24, %25, %26, %27, %28, %29, %30, %31, %32, %33, %34, %35, %36, %37, %38, %39, %40, %41, %42, %43, %44, %45, %46, %47, %48, %49, %50, %51, %52, %53, %54, %55, %56, %57, %58, %59, %60, %61, %62, %63}, {%64,%65,%66,%67}, %68, p, 1, 1, %70;\n}\n"
    : "+f"(d[0]), "+f"(d[1]), "+f"(d[2]), "+f"(d[3]), "+f"(d[4]), "+f"(d[5]), "+f"(d[6]), "+f"(d[7]), "+f"(d[8]), "+f"(d[9]), "+f"(d[10]), "+f"(d[11]), "+f"(d[12]), "+f"(d[13]), "+f"(d[14]), "+f"(d[15]), "+f"(d[16]), "+f"(d[17]), "+f"(d[18]), "+f"(d[19]), "+f"(d[20]), "+f"(d[21]), "+f"(d[22]), "+f"(d[23]), "+f"(d[24]), "+f"(d[25]), "+f"(d[26]), "+f"(d[27]), "+f"(d[28]), "+f"(d[29]), "+f"(d[30]), "+f"(d[31]), "+f"(d[32]), "+f"(d[33]), "+f"(d[34]), "+f"(d[35]), "+f"(d[36]), "+f"(d[37]), "+f"(d[38]), "+f"(d[39]), "+f"(d[40]), "+f"(d[41]), "+f"(d[42]), "+f"(d[43]), "+f"(d[44]), "+f"(d[45]), "+f"(d[46]), "+f"(d[47]), "+f"(d[48]), "+f"(d[49]), "+f"(d[50]), "+f"(d[51]), "+f"(d[52]), "+f"(d[53]), "+f"(d[54]), "+f"(d[55]), "+f"(d[56]), "+f"(d[57]), "+f"(d[58]), "+f"(d[59]), "+f"(d[60]), "+f"(d[61]), "+f"(d[62]), "+f"(d[63])
    : "r"(a0), "r"(a1), "r"(a2), "r"(a3), "l"(db), "r"(sd), "n"(TB));
}
template<int TB> DEVI void wgmma_rs_n128z(float (&d)[64], uint32_t a0, uint32_t a1, uint32_t a2, uint32_t a3, uint64_t db){
  asm volatile("{\n.reg .pred p;\nsetp.ne.b32 p, 0, 0;\n"
    "wgmma.mma_async.sync.aligned.m64n128k16.f32.bf16.bf16 {%0, %1, %2, %3, %4, %5, %6, %7, %8, %9, %10, %11, %12, %13, %14, %15, %16, %17, %18, %19, %20, %21, %22, %23, %24, %25, %26, %27, %28, %29, %30, %31, %32, %33, %34, %35, %36, %37, %38, %39, %40, %41, %42, %43, %44, %45, %46, %47, %48, %49, %50, %51, %52, %53, %54, %55, %56, %57, %58, %59, %60, %61, %62, %63}, {%64,%65,%66,%67}, %68, p, 1, 1, %69;\n}\n"
    : "=f"(d[0]), "=f"(d[1]), "=f"(d[2]), "=f"(d[3]), "=f"(d[4]), "=f"(d[5]), "=f"(d[6]), "=f"(d[7]), "=f"(d[8]), "=f"(d[9]), "=f"(d[10]), "=f"(d[11]), "=f"(d[12]), "=f"(d[13]), "=f"(d[14]), "=f"(d[15]), "=f"(d[16]), "=f"(d[17]), "=f"(d[18]), "=f"(d[19]), "=f"(d[20]), "=f"(d[21]), "=f"(d[22]), "=f"(d[23]), "=f"(d[24]), "=f"(d[25]), "=f"(d[26]), "=f"(d[27]), "=f"(d[28]), "=f"(d[29]), "=f"(d[30]), "=f"(d[31]), "=f"(d[32]), "=f"(d[33]), "=f"(d[34]), "=f"(d[35]), "=f"(d[36]), "=f"(d[37]), "=f"(d[38]), "=f"(d[39]), "=f"(d[40]), "=f"(d[41]), "=f"(d[42]), "=f"(d[43]), "=f"(d[44]), "=f"(d[45]), "=f"(d[46]), "=f"(d[47]), "=f"(d[48]), "=f"(d[49]), "=f"(d[50]), "=f"(d[51]), "=f"(d[52]), "=f"(d[53]), "=f"(d[54]), "=f"(d[55]), "=f"(d[56]), "=f"(d[57]), "=f"(d[58]), "=f"(d[59]), "=f"(d[60]), "=f"(d[61]), "=f"(d[62]), "=f"(d[63])
    : "r"(a0), "r"(a1), "r"(a2), "r"(a3), "l"(db), "n"(TB));
}
template<int TA, int TB> DEVI void wgmma_ss_n128(float (&d)[64], uint64_t da, uint64_t db, int sd){
  asm volatile("{\n.reg .pred p;\nsetp.ne.b32 p, %66, 0;\n"
    "wgmma.mma_async.sync.aligned.m64n128k16.f32.bf16.bf16 {%0, %1, %2, %3, %4, %5, %6, %7, %8, %9, %10, %11, %12, %13, %14, %15, %16, %17, %18, %19, %20, %21, %22, %23, %24, %25, %26, %27, %28, %29, %30, %31, %32, %33, %34, %35, %36, %37, %38, %39, %40, %41, %42, %43, %44, %45, %46, %47, %48, %49, %50, %51, %52, %53, %54, %55, %56, %57, %58, %59, %60, %61, %62, %63}, %64, %65, p, 1, 1, %67, %68;\n}\n"
    : "+f"(d[0]), "+f"(d[1]), "+f"(d[2]), "+f"(d[3]), "+f"(d[4]), "+f"(d[5]), "+f"(d[6]), "+f"(d[7]), "+f"(d[8]), "+f"(d[9]), "+f"(d[10]), "+f"(d[11]), "+f"(d[12]), "+f"(d[13]), "+f"(d[14]), "+f"(d[15]), "+f"(d[16]), "+f"(d[17]), "+f"(d[18]), "+f"(d[19]), "+f"(d[20]), "+f"(d[21]), "+f"(d[22]), "+f"(d[23]), "+f"(d[24]), "+f"(d[25]), "+f"(d[26]), "+f"(d[27]), "+f"(d[28]), "+f"(d[29]), "+f"(d[30]), "+f"(d[31]), "+f"(d[32]), "+f"(d[33]), "+f"(d[34]), "+f"(d[35]), "+f"(d[36]), "+f"(d[37]), "+f"(d[38]), "+f"(d[39]), "+f"(d[40]), "+f"(d[41]), "+f"(d[42]), "+f"(d[43]), "+f"(d[44]), "+f"(d[45]), "+f"(d[46]), "+f"(d[47]), "+f"(d[48]), "+f"(d[49]), "+f"(d[50]), "+f"(d[51]), "+f"(d[52]), "+f"(d[53]), "+f"(d[54]), "+f"(d[55]), "+f"(d[56]), "+f"(d[57]), "+f"(d[58]), "+f"(d[59]), "+f"(d[60]), "+f"(d[61]), "+f"(d[62]), "+f"(d[63])
    : "l"(da), "l"(db), "r"(sd), "n"(TA), "n"(TB));
}
template<int TA, int TB> DEVI void wgmma_ss_n128z(float (&d)[64], uint64_t da, uint64_t db){
  asm volatile("{\n.reg .pred p;\nsetp.ne.b32 p, 0, 0;\n"
    "wgmma.mma_async.sync.aligned.m64n128k16.f32.bf16.bf16 {%0, %1, %2, %3, %4, %5, %6, %7, %8, %9, %10, %11, %12, %13, %14, %15, %16, %17, %18, %19, %20, %21, %22, %23, %24, %25, %26, %27, %28, %29, %30, %31, %32, %33, %34, %35, %36, %37, %38, %39, %40, %41, %42, %43, %44, %45, %46, %47, %48, %49, %50, %51, %52, %53, %54, %55, %56, %57, %58, %59, %60, %61, %62, %63}, %64, %65, p, 1, 1, %66, %67;\n}\n"
    : "=f"(d[0]), "=f"(d[1]), "=f"(d[2]), "=f"(d[3]), "=f"(d[4]), "=f"(d[5]), "=f"(d[6]), "=f"(d[7]), "=f"(d[8]), "=f"(d[9]), "=f"(d[10]), "=f"(d[11]), "=f"(d[12]), "=f"(d[13]), "=f"(d[14]), "=f"(d[15]), "=f"(d[16]), "=f"(d[17]), "=f"(d[18]), "=f"(d[19]), "=f"(d[20]), "=f"(d[21]), "=f"(d[22]), "=f"(d[23]), "=f"(d[24]), "=f"(d[25]), "=f"(d[26]), "=f"(d[27]), "=f"(d[28]), "=f"(d[29]), "=f"(d[30]), "=f"(d[31]), "=f"(d[32]), "=f"(d[33]), "=f"(d[34]), "=f"(d[35]), "=f"(d[36]), "=f"(d[37]), "=f"(d[38]), "=f"(d[39]), "=f"(d[40]), "=f"(d[41]), "=f"(d[42]), "=f"(d[43]), "=f"(d[44]), "=f"(d[45]), "=f"(d[46]), "=f"(d[47]), "=f"(d[48]), "=f"(d[49]), "=f"(d[50]), "=f"(d[51]), "=f"(d[52]), "=f"(d[53]), "=f"(d[54]), "=f"(d[55]), "=f"(d[56]), "=f"(d[57]), "=f"(d[58]), "=f"(d[59]), "=f"(d[60]), "=f"(d[61]), "=f"(d[62]), "=f"(d[63])
    : "l"(da), "l"(db), "n"(TA), "n"(TB));
}
template<int TB> DEVI void wgmma_rs_n40(float (&d)[20], uint32_t a0, uint32_t a1, uint32_t a2, uint32_t a3, uint64_t db, int sd){
  asm volatile("{\n.reg .pred p;\nsetp.ne.b32 p, %25, 0;\n"
    "wgmma.mma_async.sync.aligned.m64n40k16.f32.bf16.bf16 {%0, %1, %2, %3, %4, %5, %6, %7, %8, %9, %10, %11, %12, %13, %14, %15, %16, %17, %18, %19}, {%20,%21,%22,%23}, %24, p, 1, 1, %26;\n}\n"
    : "+f"(d[0]), "+f"(d[1]), "+f"(d[2]), "+f"(d[3]), "+f"(d[4]), "+f"(d[5]), "+f"(d[6]), "+f"(d[7]), "+f"(d[8]), "+f"(d[9]), "+f"(d[10]), "+f"(d[11]), "+f"(d[12]), "+f"(d[13]), "+f"(d[14]), "+f"(d[15]), "+f"(d[16]), "+f"(d[17]), "+f"(d[18]), "+f"(d[19])
    : "r"(a0), "r"(a1), "r"(a2), "r"(a3), "l"(db), "r"(sd), "n"(TB));
}
template<int TB> DEVI void wgmma_rs_n40z(float (&d)[20], uint32_t a0, uint32_t a1, uint32_t a2, uint32_t a3, uint64_t db){
  asm volatile("{\n.reg .pred p;\nsetp.ne.b32 p, 0, 0;\n"
    "wgmma.mma_async.sync.aligned.m64n40k16.f32.bf16.bf16 {%0, %1, %2, %3, %4, %5, %6, %7, %8, %9, %10, %11, %12, %13, %14, %15, %16, %17, %18, %19}, {%20,%21,%22,%23}, %24, p, 1, 1, %25;\n}\n"
    : "=f"(d[0]), "=f"(d[1]), "=f"(d[2]), "=f"(d[3]), "=f"(d[4]), "=f"(d[5]), "=f"(d[6]), "=f"(d[7]), "=f"(d[8]), "=f"(d[9]), "=f"(d[10]), "=f"(d[11]), "=f"(d[12]), "=f"(d[13]), "=f"(d[14]), "=f"(d[15]), "=f"(d[16]), "=f"(d[17]), "=f"(d[18]), "=f"(d[19])
    : "r"(a0), "r"(a1), "r"(a2), "r"(a3), "l"(db), "n"(TB));
}
template<int TA, int TB> DEVI void wgmma_ss_n40(float (&d)[20], uint64_t da, uint64_t db, int sd){
  asm volatile("{\n.reg .pred p;\nsetp.ne.b32 p, %22, 0;\n"
    "wgmma.mma_async.sync.aligned.m64n40k16.f32.bf16.bf16 {%0, %1, %2, %3, %4, %5, %6, %7, %8, %9, %10, %11, %12, %13, %14, %15, %16, %17, %18, %19}, %20, %21, p, 1, 1, %23, %24;\n}\n"
    : "+f"(d[0]), "+f"(d[1]), "+f"(d[2]), "+f"(d[3]), "+f"(d[4]), "+f"(d[5]), "+f"(d[6]), "+f"(d[7]), "+f"(d[8]), "+f"(d[9]), "+f"(d[10]), "+f"(d[11]), "+f"(d[12]), "+f"(d[13]), "+f"(d[14]), "+f"(d[15]), "+f"(d[16]), "+f"(d[17]), "+f"(d[18]), "+f"(d[19])
    : "l"(da), "l"(db), "r"(sd), "n"(TA), "n"(TB));
}
template<int TA, int TB> DEVI void wgmma_ss_n40z(float (&d)[20], uint64_t da, uint64_t db){
  asm volatile("{\n.reg .pred p;\nsetp.ne.b32 p, 0, 0;\n"
    "wgmma.mma_async.sync.aligned.m64n40k16.f32.bf16.bf16 {%0, %1, %2, %3, %4, %5, %6, %7, %8, %9, %10, %11, %12, %13, %14, %15, %16, %17, %18, %19}, %20, %21, p, 1, 1, %22, %23;\n}\n"
    : "=f"(d[0]), "=f"(d[1]), "=f"(d[2]), "=f"(d[3]), "=f"(d[4]), "=f"(d[5]), "=f"(d[6]), "=f"(d[7]), "=f"(d[8]), "=f"(d[9]), "=f"(d[10]), "=f"(d[11]), "=f"(d[12]), "=f"(d[13]), "=f"(d[14]), "=f"(d[15]), "=f"(d[16]), "=f"(d[17]), "=f"(d[18]), "=f"(d[19])
    : "l"(da), "l"(db), "n"(TA), "n"(TB));
}
template<int TB> DEVI void wgmma_rs_n32(float (&d)[16], uint32_t a0, uint32_t a1, uint32_t a2, uint32_t a3, uint64_t db, int sd){
  asm volatile("{\n.reg .pred p;\nsetp.ne.b32 p, %21, 0;\n"
    "wgmma.mma_async.sync.aligned.m64n32k16.f32.bf16.bf16 {%0, %1, %2, %3, %4, %5, %6, %7, %8, %9, %10, %11, %12, %13, %14, %15}, {%16,%17,%18,%19}, %20, p, 1, 1, %22;\n}\n"
    : "+f"(d[0]), "+f"(d[1]), "+f"(d[2]), "+f"(d[3]), "+f"(d[4]), "+f"(d[5]), "+f"(d[6]), "+f"(d[7]), "+f"(d[8]), "+f"(d[9]), "+f"(d[10]), "+f"(d[11]), "+f"(d[12]), "+f"(d[13]), "+f"(d[14]), "+f"(d[15])
    : "r"(a0), "r"(a1), "r"(a2), "r"(a3), "l"(db), "r"(sd), "n"(TB));
}
template<int TB> DEVI void wgmma_rs_n32z(float (&d)[16], uint32_t a0, uint32_t a1, uint32_t a2, uint32_t a3, uint64_t db){
  asm volatile("{\n.reg .pred p;\nsetp.ne.b32 p, 0, 0;\n"
    "wgmma.mma_async.sync.aligned.m64n32k16.f32.bf16.bf16 {%0, %1, %2, %3, %4, %5, %6, %7, %8, %9, %10, %11, %12, %13, %14, %15}, {%16,%17,%18,%19}, %20, p, 1, 1, %21;\n}\n"
    : "=f"(d[0]), "=f"(d[1]), "=f"(d[2]), "=f"(d[3]), "=f"(d[4]), "=f"(d[5]), "=f"(d[6]), "=f"(d[7]), "=f"(d[8]), "=f"(d[9]), "=f"(d[10]), "=f"(d[11]), "=f"(d[12]), "=f"(d[13]), "=f"(d[14]), "=f"(d[15])
    : "r"(a0), "r"(a1), "r"(a2), "r"(a3), "l"(db), "n"(TB));
}
template<int TB> DEVI void wgmma_rs_n64(float (&d)[32], uint32_t a0, uint32_t a1, uint32_t a2, uint32_t a3, uint64_t db, int sd){
  asm volatile("{\n.reg .pred p;\nsetp.ne.b32 p, %37, 0;\n"
    "wgmma.mma_async.sync.aligned.m64n64k16.f32.bf16.bf16 {%0, %1, %2, %3, %4, %5, %6, %7, %8, %9, %10, %11, %12, %13, %14, %15, %16, %17, %18, %19, %20, %21, %22, %23, %24, %25, %26, %27, %28, %29, %30, %31}, {%32,%33,%34,%35}, %36, p, 1, 1, %38;\n}\n"
    : "+f"(d[0]), "+f"(d[1]), "+f"(d[2]), "+f"(d[3]), "+f"(d[4]), "+f"(d[5]), "+f"(d[6]), "+f"(d[7]), "+f"(d[8]), "+f"(d[9]), "+f"(d[10]), "+f"(d[11]), "+f"(d[12]), "+f"(d[13]), "+f"(d[14]), "+f"(d[15]), "+f"(d[16]), "+f"(d[17]), "+f"(d[18]), "+f"(d[19]), "+f"(d[20]), "+f"(d[21]), "+f"(d[22]), "+f"(d[23]), "+f"(d[24]), "+f"(d[25]), "+f"(d[26]), "+f"(d[27]), "+f"(d[28]), "+f"(d[29]), "+f"(d[30]), "+f"(d[31])
    : "r"(a0), "r"(a1), "r"(a2), "r"(a3), "l"(db), "r"(sd), "n"(TB));
}
template<int TB> DEVI void wgmma_rs_n64z(float (&d)[32], uint32_t a0, uint32_t a1, uint32_t a2, uint32_t a3, uint64_t db){
  asm volatile("{\n.reg .pred p;\nsetp.ne.b32 p, 0, 0;\n"
    "wgmma.mma_async.sync.aligned.m64n64k16.f32.bf16.bf16 {%0, %1, %2, %3, %4, %5, %6, %7, %8, %9, %10, %11, %12, %13, %14, %15, %16, %17, %18, %19, %20, %21, %22, %23, %24, %25, %26, %27, %28, %29, %30, %31}, {%32,%33,%34,%35}, %36, p, 1, 1, %37;\n}\n"
    : "=f"(d[0]), "=f"(d[1]), "=f"(d[2]), "=f"(d[3]), "=f"(d[4]), "=f"(d[5]), "=f"(d[6]), "=f"(d[7]), "=f"(d[8]), "=f"(d[9]), "=f"(d[10]), "=f"(d[11]), "=f"(d[12]), "=f"(d[13]), "=f"(d[14]), "=f"(d[15]), "=f"(d[16]), "=f"(d[17]), "=f"(d[18]), "=f"(d[19]), "=f"(d[20]), "=f"(d[21]), "=f"(d[22]), "=f"(d[23]), "=f"(d[24]), "=f"(d[25]), "=f"(d[26]), "=f"(d[27]), "=f"(d[28]), "=f"(d[29]), "=f"(d[30]), "=f"(d[31])
    : "r"(a0), "r"(a1), "r"(a2), "r"(a3), "l"(db), "n"(TB));
}

__device__ __align__(1024) bf16 g_q[32*2048*32];
__device__ __align__(1024) bf16 g_kvb[32*16*2*128*32];
__device__ __align__(1024) bf16 g_o[2048*2048];
__device__ __align__(16) float g_kv[2*32*64*40];
__device__ __align__(1024) uint4 g_kvi[8*1280];
__device__ __align__(16) unsigned g_cnt[192];
__device__ unsigned g_tile[32*16];
__device__ unsigned g_epoch;
__device__ float g_gate[2048];
constexpr int C_KV=0, C_KI=8, C_OA=16, C_OB=32, C_G=96, C_OP=128;

constexpr float LOG2E = 1.4426950408889634f;
constexpr float SC = 0.17677669529663687f*LOG2E;
constexpr float OFFS = 88.f;
constexpr uint32_t HI64 = (512u>>4)|(2u<<30);
constexpr uint32_t HI128 = (1024u>>4)|(1u<<30);
constexpr uint32_t SB = 1024;

#define RAV 144
#define RGV 192
#define PAV 3
#define PARTV 12
#define NF 32
#define NPRE 2
#define THR 3
#define NSL 100
#define DLY 0
#define GCG 1
#define GW 1
namespace k2 {
  constexpr int NST=4, GST=4;
  constexpr uint32_t SQ=SB, SKV=SQ+16384, SG=SKV+NST*16384, SW=SG+GST*32768, SO=SW+8192, SONES=SO+8192, SGATE=SONES+1024, BARS=SGATE+512;
  constexpr uint32_t B_KF=BARS, B_KE=BARS+32, B_Q=BARS+64, B_W=BARS+80, B_GF=BARS+128, B_GE=BARS+192, B_PF=BARS+256, B_PE=BARS+320, B_E=BARS+96, B_X=BARS+104, B_O=BARS+112, SEP=BARS+384;
  constexpr uint32_t PST=49152, PR=SQ;
  constexpr uint32_t SMEM=BARS+512-SB;
  constexpr int RA=RAV, RG=RGV, RP=512-2*RAV-RGV;
  constexpr int PA=PAV, PART=PARTV;
}
struct Maps { CUtensorMap x, wa, go, gos, woa, wob, out, wphi, wb; const bf16 *xp, *gw; };

DEVI void mnmx(const float (&p)[16], float& x0, float& x1, float& n0, float& n1){
  x0=fmaxf(p[0],p[1]); n0=fminf(p[0],p[1]); x1=fmaxf(p[2],p[3]); n1=fminf(p[2],p[3]);
  #pragma unroll
  for(int j=1;j<4;j++){ x0=fmaxf(x0,fmaxf(p[4*j],p[4*j+1])); n0=fminf(n0,fminf(p[4*j],p[4*j+1])); x1=fmaxf(x1,fmaxf(p[4*j+2],p[4*j+3])); n1=fminf(n1,fminf(p[4*j+2],p[4*j+3])); }
  #pragma unroll
  for(int o=1;o<4;o<<=1){ x0=fmaxf(x0,__shfl_xor_sync(0xffffffffu,x0,o)); x1=fmaxf(x1,__shfl_xor_sync(0xffffffffu,x1,o));
                          n0=fminf(n0,__shfl_xor_sync(0xffffffffu,n0,o)); n1=fminf(n1,__shfl_xor_sync(0xffffffffu,n1,o)); }
}

__global__ void __launch_bounds__(512,1) k_main(const __grid_constant__ Maps mp){
  using namespace k2;
  extern __shared__ __align__(1024) uint8_t smem_raw[];
  const uint32_t cb=smem_u32(smem_raw)-SB;
  if(cb&0xffffffu) asm volatile("trap;");
  const uint32_t B_KF=cb+k2::B_KF, B_KE=cb+k2::B_KE, B_Q=cb+k2::B_Q, B_W=cb+k2::B_W, B_GF=cb+k2::B_GF, B_GE=cb+k2::B_GE, SGATE=cb+k2::SGATE,
                 B_PF=cb+k2::B_PF, B_PE=cb+k2::B_PE, B_E=cb+k2::B_E, B_X=cb+k2::B_X, B_O=cb+k2::B_O, SEP=cb+k2::SEP;
  const int tid=threadIdx.x, lane=tid&31, warp=__shfl_sync(0xffffffffu,tid>>5,0);
  const int m=blockIdx.x&15, hh=blockIdx.x>>4;
  if(tid==0){
    for(int s=0;s<NST;s++){ mbar_init(B_KF+8*s,1); mbar_init(B_KE+8*s,8); }
    for(int s=0;s<GST;s++){ mbar_init(B_GF+8*s,1); mbar_init(B_GE+8*s,8); }
    mbar_init(B_E,1); mbar_init(B_X,1); mbar_init(B_O,1);
    mbar_init(B_Q,1); mbar_init(B_Q+8,1); mbar_init(B_W,1); mbar_init(B_W+8,1);
    asm volatile("fence.mbarrier_init.release.cluster;":::"memory"); }
  if(tid==416){
    for(int s=0;s<4;s++){ mbar_init(B_PF+8*s,1); mbar_init(B_PE+8*s,16); }
    asm volatile("fence.mbarrier_init.release.cluster;":::"memory"); fence_async_smem();
    for(int s=0;s<4;s++){ const uint32_t a=cb+PR+s*PST; mbar_expect_tx(B_PF+8*s,PST); tma2d(a,&mp.x,s*64,m*128,B_PF+8*s);
      if(s<NPRE) for(int b=0;b<4;b++) tma2d(a+16384+b*8192,&mp.wb,(b<3 ? b*1024 : 2112)+hh*128,s*64,B_PF+8*s); }
  }
  if(tid<256) asm volatile("st.shared.u32 [%0], %1;"::"r"(cb+SONES+tid*4),"r"(0x3F803F80u):"memory");
  cluster_sync();
  auto epoch=[&]{ mbar_wait(B_E,0); uint32_t e; asm volatile("ld.shared.u32 %0, [%1];":"=r"(e):"r"(SEP):"memory"); return e; };

  if(warp>=12){
    reg_dealloc<RP>();
    if(warp==12){
      const uint32_t tag=epoch();
      bar_sync(3,320);
      if(lane==0){
        const uint32_t pr=(m&1)^1;
        mbar_arrive_cl(mapa(B_X,pr));
        mbar_arrive(B_KF); mbar_expect_tx(B_KF+8,16384);
        mbar_wait(B_X,0);
        asm volatile("cp.async.bulk.shared::cluster.shared::cta.mbarrier::complete_tx::bytes [%0], [%1], %2, [%3];"::"r"(mapa(cb+SKV+16384,pr)),"r"(cb+SKV),"r"(16384),"r"(mapa(B_KF+8,pr)):"memory");
        if(DLY) __nanosleep(DLY);
        bulk_s2g(g_kvb+((size_t)(4*hh+1)*16+m)*8192, cb+SKV+3*16384, 16384);
        #pragma unroll
        for(int j=0;j<2;j++) bulk_s2g(g_kvb+((size_t)(4*hh+2+j)*16+m)*8192+4096, cb+SW+j*8192, 8192);
        bulk_commit();
      }
      uint32_t ready=0;
      #pragma unroll 1
      for(int it=2;it<64;it++){ const int h=4*hh+(it>>4), t=(it+(m&14))&15, sl=it&3;
        if((it&15)==0) ready=0;
        if(!((ready>>t)&1)){
          for(int i=0;;i++){ unsigned v; asm volatile("ld.relaxed.gpu.global.u32 %0, [%1];":"=r"(v):"l"(&g_tile[h*16+(lane&15)]):"memory");
            ready=__ballot_sync(0xffffffffu, v==tag); if((ready>>t)&1) break; if(i>(1<<22)) asm volatile("trap;"); __nanosleep(NSL); }
          asm volatile("fence.acq_rel.cta;":::"memory"); fence_async_all();
          }
        if(lane==0){
          if(it==3) bulk_wait_read<0>();
          if(it==4){ bulk_wait<0>(); flag_set_rlx(&g_tile[(4*hh+1)*16+m],tag); flag_wait_eq(&g_tile[(4*hh)*16+m],tag);
            mbar_wait(B_KF+8,0); mbar_arrive_cl(mapa(B_X,(m&1)^1));
            mbar_wait(B_X,1); }
          mbar_wait(B_KE+8*sl,((it>>2)&1)^1); mbar_expect_tx(B_KF+8*sl,16384);
          bulk_g2s(cb+SKV+sl*16384, g_kvb+((size_t)h*16+t)*8192, 16384, B_KF+8*sl);
          if(it==THR){
            #pragma unroll
            for(int i=0;i<8;i++) mbar_arrive_cl(mapa(B_GE+24,i&1)); }
          if(it==3){ mbar_expect_tx(B_W,8192); tma2d(cb+SW,&mp.wphi,0,hh*128,B_W); }
          if(it==16+NST || it==32+NST){ const int r=(it>>4)&1^1;
            flag_wait_eq(&g_tile[(h+1)*16+m],tag); fence_async_all();
            mbar_expect_tx(B_Q+8*r,8192); bulk_g2s(cb+SQ+r*8192, g_q+((size_t)(h+1)*2048+m*128)*32, 8192, B_Q+8*r); } }
        __syncwarp(); }
    } else if(warp==13){
      if(lane==0){
        const uint32_t rank=m&1;
        #pragma unroll 1
        for(int it=NPRE;it<16;it++){ const int s=it&3, k=it*64; const uint32_t a=cb+PR+s*PST, bar=B_PF+8*s;
          if(it>=4){ mbar_wait(B_PE+8*s,((it>>2)&1)^1); mbar_expect_tx(bar,PST); tma2d(a,&mp.x,k,m*128,bar); }
          tma2d_mc(a+16384+rank*16384,&mp.wb,rank*2048+hh*128,k,bar,3);
          tma2d_mc(a+24576+rank*16384,&mp.wb,(rank ? 2112 : 1024)+hh*128,k,bar,3); }
        const uint32_t tag=epoch();
        #pragma unroll 1
        for(int it=0;it<93;it++){
          const int s=it&3; const uint32_t a=cb+SG+s*32768, bar=B_GF+8*s;
          mbar_wait(B_GE+8*s,(it>>2)&1);
          if(it<64){
            const int job=it>>4, k=(it&15)*64, n = job==0 ? rank*1024+hh*128+64 : job<3 ? 1024+rank*1024+hh*128+(job-1)*64 : hh*128+rank*64;
            mbar_expect_tx(bar,32768); tma2d_mc(a+16384+rank*8192,job==0 ? &mp.wb : &mp.wa,n,k,bar,3); tma2d(a,&mp.x,k,m*128,bar);
          } else if(it==64){
            flag_wait(&g_cnt[C_KI+hh],16*tag); fence_async_all();
            mbar_expect_tx(bar,20480); bulk_g2s(a,g_kvi+hh*1280,20480,bar);
          } else {
            const int j=it-65, k = j<8 ? 1024+j*64 : j<24 ? (j-8)*64 : 1024+(j-16)*64;
            mbar_expect_tx(bar,32768);
            if(k<1024) tma2d_mc(a+16384+rank*8192,&mp.woa,hh*128+rank*64,k,bar,3);
            else tma4d_mc(a+16384+rank*8192,&mp.wob,hh*128+rank*64,0,(k-1024)>>8,(k&255)>>5,bar,3);
            if(k==0){ flag_wait(&g_cnt[C_OA+m],8*tag); fence_async_all(); }
            if(k>=1024 && (k&255)==0){ flag_wait(&g_cnt[C_OB+((k-1024)>>8)*16+m],8*tag); fence_async_all(); }
            tma2d(a,&mp.go,k,m*128,bar);
          } }
        uint32_t todo=15;
        #pragma unroll 1
        for(int it=93;it<97;it++){
          const int s=it&3; const uint32_t a=cb+SG+s*32768, bar=B_GF+8*s;
          mbar_wait(B_GE+8*s,(it>>2)&1);
          uint32_t rdy=0;
          for(int i=0;!rdy;i++){ uint32_t c0,c1,c2,c3;
            asm volatile("ld.relaxed.gpu.global.v4.u32 {%0,%1,%2,%3}, [%4];":"=r"(c0),"=r"(c1),"=r"(c2),"=r"(c3):"l"(&g_cnt[C_OP+4*m]):"memory");
            rdy=todo&((c0==2*tag)|(c1==2*tag)<<1|(c2==2*tag)<<2|(c3==2*tag)<<3);
            if(i>(1<<22)) asm volatile("trap;"); }
          const int p=__ffs(rdy)-1; todo&=~(1u<<p);
          asm volatile("fence.acq_rel.cta;":::"memory"); fence_async_all();
          mbar_expect_tx(bar,32768);
          tma2d(a,&mp.go,1792+p*64,m*128,bar);
          tma4d(a+16384,&mp.wob,hh*128,0,3,2*p,bar); tma4d(a+24576,&mp.wob,hh*128+64,0,3,2*p,bar);
 }
      }
    } else if(warp==14){
      const uint32_t tag=epoch();
      bar_sync(3,320);
      if(lane==0){ bulk_s2g(g_kvb+((size_t)(4*hh)*16+m)*8192, cb+SKV, 16384); bulk_commit(); bulk_wait<0>();
        flag_set_rlx(&g_tile[(4*hh)*16+m],tag);
        flag_wait(&g_cnt[C_G+m],8*tag); }
      __syncwarp();
      #pragma unroll
      for(int i=0;i<4;i++) asm volatile("st.shared.f32 [%0], %1;"::"r"(SGATE+(i*32+lane)*4),"f"(__ldcg(g_gate+m*128+i*32+lane)):"memory");
      __syncwarp(); if(lane==0) mbar_arrive(B_W+8);
      for(int r=0;r<4;r++){ bar_sync(2,288);
        if(lane==0){ tma2d_store(&mp.gos,cb+SO,1024+r*256+hh*32,m*128); bulk_commit(); bulk_wait<0>();
          flag_add_rlx(&g_cnt[r<3 ? C_OB+r*16+m : C_OP+4*m+(hh>>1)]); mbar_arrive(B_O); }
        __syncwarp(); }
    } else {
      const uint32_t tag=ld_acq(&g_epoch)+1;
      if(lane==0){ asm volatile("st.shared.u32 [%0], %1;"::"r"(SEP),"r"(tag):"memory"); mbar_arrive(B_E); }
      #pragma unroll
      for(int i=0;i<5;i++) *(float4*)(g_kv+((tag+1)&1)*81920+blockIdx.x*640+i*128+lane*4)=make_float4(0.f,0.f,0.f,0.f);
      if(lane==0) flag_wait_eq(&g_tile[(4*hh+1)*16+m],tag);
      bar_sync(4,160);
      if(lane==0){
        #pragma unroll
        for(int j=0;j<2;j++){ bulk_s2g(g_q+((size_t)(4*hh+2+j)*2048+m*128)*32, cb+SG+3*32768+j*8192, 8192); bulk_s2g(g_kvb+((size_t)(4*hh+2+j)*16+m)*8192, cb+SG+3*32768+16384+j*8192, 8192); }
        bulk_commit(); bulk_wait_read<0>(); }
      __syncwarp();
      if(lane<8) mbar_arrive_cl(mapa(B_GE+24,lane&1));
      if(lane==0){ bulk_wait<0>(); flag_set_rlx(&g_tile[(4*hh+2)*16+m],tag); flag_set_rlx(&g_tile[(4*hh+3)*16+m],tag); }
      bar_sync(4,160);
      if(lane==0){ flag_add(&g_cnt[C_KV+hh]); flag_wait(&g_cnt[C_KV+hh],16*tag); }
      __syncwarp();
      const int f=m*16+(lane>>1), c0=(lane&1)*2; const float* src=g_kv+(tag&1)*81920+((size_t)hh*256+f)*40;
      #pragma unroll
      for(int c=c0;c<c0+2;c++){ const float4 a=__ldcg((const float4*)(src+c*8)), b=__ldcg((const float4*)(src+c*8+4));
        g_kvi[hh*1280+f*4+(c^((f>>1)&3))]=make_uint4(pack(a.x,a.y),pack(a.z,a.w),pack(b.x,b.y),pack(b.z,b.w)); }
      if((lane&1)==0) g_kvi[hh*1280+1024+(f&63)*4+((f>>6)^((f>>1)&3))]=make_uint4(pack(__ldcg(src+32),1.f),0u,0u,0u);
      __syncwarp();
      if(lane==0){ flag_add(&g_cnt[C_KI+hh]); }
      bar_sync(4,160);
      if(lane==0){ tma2d_store(&mp.go,cb+SG+3*32768,hh*128,m*128); tma2d_store(&mp.go,cb+SG+3*32768+16384,hh*128+64,m*128); bulk_commit(); bulk_wait_read<0>(); }
      __syncwarp();
      if(lane<8) mbar_arrive_cl(mapa(B_GE+24,lane&1));
      if(lane==0){ bulk_wait<0>(); flag_add_rlx(&g_cnt[C_OA+m]); }
    }
  } else if(warp>=8){
    const int wq=warp-8, t128=tid-256;
    uint32_t zz; asm volatile("mov.u32 %0, 0;":"=r"(zz)); zz=__shfl_sync(0xffffffffu,zz,0);
    int s=0; uint32_t ph=0;
    const uint32_t rel=mapa(B_GE,lane&1);
    auto release=[&](int slot){ if(lane<2) mbar_arrive_cl(rel+8*slot); };
    const int srow=wq*16+(lane&15);
    {
      #pragma unroll 1
      for(int r=0;r<4;r++){ const int row=m*128+hh*16+wq*4+r; float gs=0;
        #pragma unroll
        for(int j=0;j<4;j++){ const uint4 a=__ldg((const uint4*)(mp.xp+(size_t)row*1024+j*256+lane*8)), b=__ldg((const uint4*)(mp.gw+j*256+lane*8));
          const __nv_bfloat162* pa=(const __nv_bfloat162*)&a; const __nv_bfloat162* pb=(const __nv_bfloat162*)&b;
          #pragma unroll
          for(int e=0;e<4;e++){ float2 p=__bfloat1622float2(__hmul2(pa[e],pb[e])); gs+=p.x+p.y; } }
        #pragma unroll
        for(int o=16;o;o>>=1) gs+=__shfl_xor_sync(0xffffffffu,gs,o);
        gs=__bfloat162float(__float2bfloat16(gs));
        if(lane==0) g_gate[row]=__bfloat162float(__float2bfloat16(1.f/(1.f+__expf(-gs)))); }
      bar_sync(1,128);
      if(t128==0) flag_add(&g_cnt[C_G+m]);
      bar_sync(5,384);
      #pragma unroll
      for(int i=0;i<(THR ? 3 : 4);i++) release(i);
    }
    reg_alloc<RG>();
    #pragma unroll 1
    for(int job=-1;job<4;job++){
      float acc[2][64];
      auto stage=[&](const bool z, const bool rl, const int G, const int W){
        mbar_wait(B_GF+8*s,ph);
        const uint32_t ad=((SG+s*32768)>>4)|(1u<<16), bd=((SG+s*32768+16384)>>4)|((8192u>>4)<<16);
        auto wt=[&]{ wg_commit(); if(W) wg_wait<1>(); else wg_wait<0>(); };
        #pragma unroll
        for(int kk=0;kk<4;kk++){
          if(G==0 || kk%(G?G:1)==0) wg_fence();
          if(z&&kk==0) wgmma_ss_n128z<0,1>(acc[0],mk_desc2(ad,HI128),mk_desc2(bd,HI128));
          else wgmma_ss_n128<0,1>(acc[0],mk_desc2(ad+kk*2,HI128),mk_desc2(bd+kk*128,HI128),1);
          if(G==0){ wt(); if(rl && kk==0) release((s+3)&3); wg_fence(); }
          if(z&&kk==0) wgmma_ss_n128z<0,1>(acc[1],mk_desc2(ad+512,HI128),mk_desc2(bd,HI128));
          else wgmma_ss_n128<0,1>(acc[1],mk_desc2(ad+512+kk*2,HI128),mk_desc2(bd+kk*128,HI128),1);
          if(G==0 || kk%(G?G:1)==G-1){ wt(); if(rl && kk==G-1) release((s+3)&3); }
        }
        s=(s+1)&3; ph^=(s==0); };
      stage(true,false,GCG,GW);
      const int nst = job==3 ? 32 : 16;
      #pragma unroll 1
      for(int st=1;st<nst;st++) stage(false,st<29,GCG,GW);
      wg_wait<0>();
      bar_sync(1,128);
      const uint32_t SCR = SG + (job<2 ? 3*32768 : 0);
      fence_regs(acc[0]); fence_regs(acc[1]);
      if(job<0){
        #pragma unroll
        for(int mb=0;mb<2;mb++){ const int row=mb*64+srow;
          #pragma unroll
          for(int c=0;c<8;c++){ const float* v=&acc[mb][8*c];
            stsm4(cb+SCR+(c>>1)*8192+row*64+((((c&1)*2+(lane>>4))^((row>>1)&3))<<4), pack(v[0],v[1]),pack(v[2],v[3]),pack(v[4],v[5]),pack(v[6],v[7])); } }
        fence_async_smem(); bar_arrive(4,160);
      } else if(job<2){
        if(job==0) mbar_wait(B_W,0);
        uint32_t kf[2][16];
        #pragma unroll
        for(int mb=0;mb<2;mb++){
          #pragma unroll
          for(int i=0;i<16;i++) kf[mb][i]=pack(acc[mb][2*i],acc[mb][2*i+1]);
          const int row=mb*64+srow;
          #pragma unroll
          for(int c=0;c<4;c++){ const float* v=&acc[mb][32+8*c];
            stsm4(cb+SCR+(c>>1)*8192+row*64+((((c&1)*2+(lane>>4))^((row>>1)&3))<<4), pack(v[0],v[1]),pack(v[2],v[3]),pack(v[4],v[5]),pack(v[6],v[7])); }
        }
        float pk[2][2][16];
        wg_fence();
        #pragma unroll
        for(int h=0;h<2;h++){ const uint32_t wd=((SW+(job*2+h)*2048)>>4)|(1u<<16);
          #pragma unroll
          for(int mb=0;mb<2;mb++){
            wgmma_rs_n32z<1>(pk[h][mb],kf[mb][8*h],kf[mb][8*h+1],kf[mb][8*h+2],kf[mb][8*h+3],mk_desc2(wd,HI64));
            wgmma_rs_n32<1>(pk[h][mb],kf[mb][8*h+4],kf[mb][8*h+5],kf[mb][8*h+6],kf[mb][8*h+7],mk_desc2(wd+64,HI64),1); } }
        wg_commit(); wg_wait<0>();
        float kv[20];
        auto put_kv=[&](int h){
          wg_wait<0>(); fence_regs(kv);
          float* dst=g_kv+(epoch()&1)*81920+((size_t)(4*hh+2*job+h)*64+wq*16+(lane>>2))*40+(lane&3)*2;
          #pragma unroll
          for(int j=0;j<4;j++){ red2(dst+8*j,kv[4*j],kv[4*j+1]); red2(dst+320+8*j,kv[4*j+2],kv[4*j+3]); }
          if((lane&3)==0){ red1(dst+32,kv[16]); red1(dst+352,kv[18]); } };
        #pragma unroll
        for(int h=0;h<2;h++){
          fence_regs(pk[h][0]); fence_regs(pk[h][1]);
          uint32_t ph_[2][16];
          #pragma unroll
          for(int mb=0;mb<2;mb++){
            float (&p)[16]=pk[h][mb]; float x0,x1,n0,n1; mnmx(p,x0,x1,n0,n1);
            x0*=-LOG2E; x1*=-LOG2E; n0*=LOG2E; n1*=LOG2E;
            float ep[16],en[16],sp0=0,sp1=0,sn0=0,sn1=0;
            #pragma unroll
            for(int i=0;i<16;i++){ const bool hi=i&2; ep[i]=ex2(fmaf(p[i],LOG2E,hi?x1:x0)); en[i]=ex2(fmaf(p[i],-LOG2E,hi?n1:n0));
              if(hi){ sp1+=ep[i]; sn1+=en[i]; } else { sp0+=ep[i]; sn0+=en[i]; } }
            #pragma unroll
            for(int o=1;o<4;o<<=1){ sp0+=__shfl_xor_sync(0xffffffffu,sp0,o); sp1+=__shfl_xor_sync(0xffffffffu,sp1,o); sn0+=__shfl_xor_sync(0xffffffffu,sn0,o); sn1+=__shfl_xor_sync(0xffffffffu,sn1,o); }
            sp0=rcp(sp0); sp1=rcp(sp1); sn0=rcp(sn0); sn1=rcp(sn1);
            #pragma unroll
            for(int i=0;i<8;i++){ const bool hi=i&1; ph_[mb][i]=pack(ep[2*i]*(hi?sp1:sp0),ep[2*i+1]*(hi?sp1:sp0)); ph_[mb][8+i]=pack(en[2*i]*(hi?sn1:sn0),en[2*i+1]*(hi?sn1:sn0)); }
          }
          if(h==1){
            #pragma unroll
            for(int i=0;i<16;i++) asm volatile(""::"r"(ph_[0][i]),"r"(ph_[1][i]));
            put_kv(0); bar_sync(1,128); }
          #pragma unroll
          for(int mb=0;mb<2;mb++){ const int row=mb*64+srow;
            #pragma unroll
            for(int c=0;c<4;c++) stsm4(cb+SCR+16384+row*128+(((2*c+(lane>>4))^(row&7))<<4), ph_[mb][4*c],ph_[mb][4*c+1],ph_[mb][4*c+2],ph_[mb][4*c+3]); }
          fence_async_smem(); bar_sync(1,128);
          const uint32_t pd=((SCR+16384)>>4)|(1u<<16), vd=((SCR+h*8192)>>4)|(((SONES-SCR-h*8192)>>4)<<16);
          wg_fence();
          wgmma_ss_n40z<1,1>(kv,mk_desc2(pd,HI128),mk_desc2(vd,HI64));
          #pragma unroll
          for(int ks=1;ks<8;ks++) wgmma_ss_n40<1,1>(kv,mk_desc2(pd+ks*128,HI128),mk_desc2(vd+ks*(64u-(64u<<16)),HI64),1);
          wg_commit();
        }
        put_kv(1);
        release(3);
        if(job==1) bar_arrive(4,160);
      } else if(job==2){
        uint32_t qf[2][32];
        #pragma unroll
        for(int mb=0;mb<2;mb++){
          #pragma unroll
          for(int i=0;i<32;i++) qf[mb][i]=pack(acc[mb][2*i],acc[mb][2*i+1]); }
        float pq[2][16], op[20], on[20]; uint32_t e[2][16];
        auto PQ=[&](const int i){ const int h=i>>1, mb=i&1; const uint32_t wd=((SW+h*2048)>>4)|(1u<<16);
          wgmma_rs_n32z<1>(pq[mb],qf[mb][8*h],qf[mb][8*h+1],qf[mb][8*h+2],qf[mb][8*h+3],mk_desc2(wd,HI64));
          wgmma_rs_n32<1>(pq[mb],qf[mb][8*h+4],qf[mb][8*h+5],qf[mb][8*h+6],qf[mb][8*h+7],mk_desc2(wd+64,HI64),1); };
        auto EX=[&](const int b){
          float (&p)[16]=pq[b]; fence_regs(p); float x0,x1,n0,n1; mnmx(p,x0,x1,n0,n1);
          x0*=-LOG2E; x1*=-LOG2E; n0*=LOG2E; n1*=LOG2E;
          #pragma unroll
          for(int i=0;i<8;i++){ const bool hi=i&1;
            e[b][i]=pack(ex2(fmaf(p[2*i],LOG2E,hi?x1:x0)),ex2(fmaf(p[2*i+1],LOG2E,hi?x1:x0)));
            e[b][8+i]=pack(ex2(fmaf(p[2*i],-LOG2E,hi?n1:n0)),ex2(fmaf(p[2*i+1],-LOG2E,hi?n1:n0))); }
          #pragma unroll
          for(int i=0;i<16;i++) asm volatile(""::"r"(e[b][i])); };
        wg_fence(); PQ(0); PQ(1); wg_commit(); wg_wait<0>();
        EX(0);
        mbar_wait(B_GF,ph); mbar_wait(B_W+8,0);
        float gt[4];
        #pragma unroll
        for(int i=0;i<4;i++) asm volatile("ld.shared.f32 %0, [%1];":"=f"(gt[i]):"r"(SGATE+((i>>1)*64+(i&1)*8+wq*16+(lane>>2))*4));
        #pragma unroll
        for(int i=0;i<8;i++){ const int h=i>>1, mb=i&1;
          const uint32_t kd=((SCR+h*4096)>>4)|(((16384+16*h-h*4096)>>4)<<16);
          wg_fence();
          wgmma_rs_n40z<1>(op,e[mb][0],e[mb][1],e[mb][2],e[mb][3],mk_desc2(kd,HI64));
          wgmma_rs_n40<1>(op,e[mb][4],e[mb][5],e[mb][6],e[mb][7],mk_desc2(kd+64,HI64),1);
          wgmma_rs_n40z<1>(on,e[mb][8],e[mb][9],e[mb][10],e[mb][11],mk_desc2(kd+128,HI64));
          wgmma_rs_n40<1>(on,e[mb][12],e[mb][13],e[mb][14],e[mb][15],mk_desc2(kd+192,HI64),1);
          if(i<6) PQ(i+2);
          wg_commit();
          if(i<7) EX(mb^1);
          BOUND(40+i);
          wg_wait<0>(); fence_regs(op); fence_regs(on);
          float a0=rcp(op[17]), b0=rcp(on[17]), a1=rcp(op[19]), b1=rcp(on[19]);
          const float f0=__fdividef(gt[2*mb],op[16]*a0+on[16]*b0+1e-6f), f1=__fdividef(gt[2*mb+1],op[18]*a1+on[18]*b1+1e-6f);
          a0=__shfl_sync(0xffffffffu,a0*f0,lane&28); b0=__shfl_sync(0xffffffffu,b0*f0,lane&28);
          a1=__shfl_sync(0xffffffffu,a1*f1,lane&28); b1=__shfl_sync(0xffffffffu,b1*f1,lane&28);
          const int row=mb*64+srow;
          #pragma unroll
          for(int c=0;c<2;c++){ const float* p=&op[8*c]; const float* n=&on[8*c];
            stsm4(cb+SG+3*32768+(h>>1)*16384+row*128+((((h&1)*4+c*2+(lane>>4))^(row&7))<<4),
                  pack(p[0]*a0+n[0]*b0,p[1]*a0+n[1]*b0),pack(p[2]*a1+n[2]*b1,p[3]*a1+n[3]*b1),pack(p[4]*a0+n[4]*b0,p[5]*a0+n[5]*b0),pack(p[6]*a1+n[6]*b1,p[7]*a1+n[7]*b1)); }
        }
        fence_async_smem();
        release(0); s=1;
        bar_arrive(4,160);
      } else {
        #pragma unroll
        for(int mb=0;mb<2;mb++){ const int row=mb*64+srow;
          #pragma unroll
          for(int c=0;c<8;c++){ const float* v=&acc[mb][8*c];
            stsm4(cb+SCR+(c>>2)*16384+row*128+((((c&3)*2+(lane>>4))^(row&7))<<4), pack(v[0],v[1]),pack(v[2],v[3]),pack(v[4],v[5]),pack(v[6],v[7])); } }
        fence_async_smem(); bar_sync(1,128);
        if(t128==0){ tma2d_store(&mp.out,cb+SCR,hh*128,m*128); tma2d_store(&mp.out,cb+SCR+16384,hh*128+64,m*128); bulk_commit();
          if(blockIdx.x==0) g_epoch=epoch();
          bulk_wait_read<0>(); }
      }
    }
  } else {
    reg_alloc<168>();
    constexpr uint32_t kd0=(SKV>>4)|(1u<<16), vd0=((SKV+8192)>>4)|(((SONES-SKV-8192)>>4)<<16);
    {
      const uint32_t prel=mapa(B_PE,lane&1); const int row=warp*16+(lane&15);
      const uint32_t so=cb+row*64, sx=(row>>1)&3;
      float acc[2][64];
      auto pa=[&](const int k, const bool z){
        const int ps=k&3;
        mbar_wait(B_PF+8*ps,(k>>2)&1);
        const uint32_t ad=((PR+ps*PST+(warp>>2)*8192)>>4)|(1u<<16), bd=((PR+ps*PST+16384)>>4)|((8192u>>4)<<16);
        wg_fence();
        #pragma unroll
        for(int kk=0;kk<4;kk++){
          #pragma unroll
          for(int nb=0;nb<2;nb++){
            if(z&&kk==0) wgmma_ss_n128z<0,1>(acc[nb],mk_desc2(ad,HI128),mk_desc2(bd+nb*1024,HI128));
            else wgmma_ss_n128<0,1>(acc[nb],mk_desc2(ad+kk*2,HI128),mk_desc2(bd+nb*1024+kk*128,HI128),1); }
          if(kk==0){ wg_commit(); wg_wait<1>(); if(!z && k<13 && lane<2) mbar_arrive_cl(prel+8*((k+3)&3)); wg_fence(); } }
        wg_commit(); };
      pa(0,true);
      #pragma unroll 1
      for(int k=1;k<16;k++) pa(k,false);
      wg_wait<0>(); fence_regs(acc[0]); fence_regs(acc[1]);
      bar_sync(5,384);
      #pragma unroll
      for(int c=0;c<16;c++){ const float* v=&acc[c>>3][8*(c&7)]; const int j=(c>>1)&1, bx=c>>2;
        stsm4(so+(bx==0 ? SQ+j*8192 : bx<3 ? SKV+j*49152+(bx-1)*8192 : SW+j*8192)+((((c&1)*2+(lane>>4))^sx)<<4), pack(v[0],v[1]),pack(v[2],v[3]),pack(v[4],v[5]),pack(v[6],v[7])); }
      fence_async_smem(); bar_sync(3,320);
    }
    reg_dealloc<RA>();
    float o[20], S0[32], S1[32], nb0=0, nb1=0; uint32_t P0[16], P1[16];
    #pragma unroll
    for(int i=0;i<20;i++) o[i]=0;
    #pragma unroll
    for(int i=0;i<16;i++) P1[i]=0;
    fence_regs(o);
    uint32_t qf[8];
    auto ldq=[&](int u){ uint32_t t; asm volatile("mov.u32 %0, %%tid.x;":"=r"(t));
      const uint32_t row=(t>>5)*16+(t&15), a=cb+SQ+(u&1)*8192+row*64;
      #pragma unroll
      for(int kk=0;kk<2;kk++) asm volatile("ldmatrix.sync.aligned.m8n8.x4.shared.b16 {%0,%1,%2,%3}, [%4];":"=r"(qf[4*kk]),"=r"(qf[4*kk+1]),"=r"(qf[4*kk+2]),"=r"(qf[4*kk+3])
        :"r"(a+(((2*kk+((t>>4)&1))^((row>>1)&3))<<4)):"memory"); };
    ldq(0);
    auto qk=[&](float (&S)[32], uint32_t kd){
      wgmma_rs_n64z<0>(S,qf[0],qf[1],qf[2],qf[3],mk_desc2(kd,HI64));
      wgmma_rs_n64<0>(S,qf[4],qf[5],qf[6],qf[7],mk_desc2(kd+2,HI64),1); };
    wg_fence(); qk(S0,kd0); wg_commit(); wg_wait<0>(); fence_regs(S0);
    auto epi=[&](int r){
      uint32_t cta,t; asm volatile("mov.u32 %0, %%ctaid.x;":"=r"(cta)); asm volatile("mov.u32 %0, %%tid.x;":"=r"(t));
      const int lr=(t>>5)*16+((t&31)>>2), head=4*(cta>>4)+r;
      if(r==0) mbar_wait(B_W+8,0);
      float g0,g1; asm volatile("ld.shared.f32 %0, [%1];":"=f"(g0):"r"(SGATE+lr*4)); asm volatile("ld.shared.f32 %0, [%1];":"=f"(g1):"r"(SGATE+lr*4+32));
      g0=__bfloat162float(__float2bfloat16(1.f-g0)); g1=__bfloat162float(__float2bfloat16(1.f-g1));
      const float f0=__fdividef(g0,o[16]), f1=__fdividef(g1,o[18]);
      if(r>0) mbar_wait(B_O,(r-1)&1);
      float t0=0,t1=0;
      #pragma unroll
      for(int j=0;j<4;j++){ t0+=fabsf(o[4*j])+fabsf(o[4*j+1]); t1+=fabsf(o[4*j+2])+fabsf(o[4*j+3]); }
      { const uint32_t row=(t>>5)*16+(t&15);
        #pragma unroll
        for(int c=0;c<2;c++){ const float* v=&o[8*c];
          stsm4(cb+SO+row*64+(((c*2+((t>>4)&1))^((row>>1)&3))<<4), pack(v[0]*f0,v[1]*f0),pack(v[2]*f1,v[3]*f1),pack(v[4]*f0,v[5]*f0),pack(v[6]*f1,v[7]*f1)); } }
      const unsigned b0=__ballot_sync(0xffffffffu,!(o[16]<1e30f && t0<3e38f)), b1=__ballot_sync(0xffffffffu,!(o[18]<1e30f && t1<3e38f));
      if(b0|b1){
        const int ln=t&31; const uint8_t* kv=(const uint8_t*)(g_kvb+(size_t)head*16*8192);
        #pragma unroll 1
        for(int rr=0;rr<16;rr++){
          if(!(((rr<8?b0:b1)>>((rr&7)*4))&15)) continue;
          const int qrow=(t>>5)*16+rr; const uint32_t qa=cb+SQ+(r&1)*8192+qrow*64;
          auto dot=[&](int key){ float s=0; const uint8_t* kr=kv+(key>>7)*16384+(key&127)*64;
            #pragma unroll 1
            for(int c=0;c<4;c++){ uint4 a=__ldcg((const uint4*)(kr+((c^((key>>1)&3))<<4))), b;
              asm volatile("ld.shared.v4.u32 {%0,%1,%2,%3}, [%4];":"=r"(b.x),"=r"(b.y),"=r"(b.z),"=r"(b.w):"r"(qa+((c^((qrow>>1)&3))<<4)));
              const uint32_t* pa=&a.x; const uint32_t* pb=&b.x;
              #pragma unroll
              for(int e=0;e<4;e++){ s=fmaf(__uint_as_float(pa[e]<<16),__uint_as_float(pb[e]<<16),s); s=fmaf(__uint_as_float(pa[e]&0xffff0000u),__uint_as_float(pb[e]&0xffff0000u),s); } }
            return s; };
          float mx=-INFINITY;
          #pragma unroll 1
          for(int k=ln;k<2048;k+=32) mx=fmaxf(mx,dot(k));
          #pragma unroll
          for(int of=16;of;of>>=1) mx=fmaxf(mx,__shfl_xor_sync(0xffffffffu,mx,of));
          float a=0,l=0;
          #pragma unroll 1
          for(int k0=0;k0<2048;k0+=32){ const float p=ex2((dot(k0+ln)-mx)*SC); l+=p;
            #pragma unroll 1
            for(int j=0;j<32;j++){ const int key=k0+j; const unsigned short vv=__ldcg((const unsigned short*)(kv+(key>>7)*16384+8192+(key&127)*64+(((ln>>3)^((key>>1)&3))<<4)+(ln&7)*2));
              a=fmaf(__shfl_sync(0xffffffffu,p,j),__uint_as_float((uint32_t)vv<<16),a); } }
          #pragma unroll
          for(int of=16;of;of>>=1) l+=__shfl_xor_sync(0xffffffffu,l,of);
          float g; asm volatile("ld.shared.f32 %0, [%1];":"=f"(g):"r"(SGATE+qrow*4));
          g=__bfloat162float(__float2bfloat16(1.f-g));
          __syncwarp();
          asm volatile("st.shared.u16 [%0], %1;"::"r"(cb+SO+qrow*64+(((ln>>3)^((qrow>>1)&3))<<4)+(ln&7)*2),"h"(__bfloat16_as_ushort(__float2bfloat16(a*g/l))):"memory");
        }
      }
      fence_async_smem(); bar_arrive(2,288);
    };
    const bool l0 = lane==0;
    uint32_t zz; asm volatile("mov.u32 %0, 0;":"=r"(zz)); zz=__shfl_sync(0xffffffffu,zz,0);
    uint32_t sp=NST-1, sc=0, sn=1, phn=0;
    auto newmax=[&](float (&S)[32]){
      float m0=S[0],m1=S[2];
      #pragma unroll
      for(int i=0;i<8;i++){ m0=fmaxf(m0,fmaxf(S[4*i],S[4*i+1])); m1=fmaxf(m1,fmaxf(S[4*i+2],S[4*i+3])); }
      m0=fmaxf(m0,__shfl_xor_sync(0xffffffffu,m0,1)); m0=fmaxf(m0,__shfl_xor_sync(0xffffffffu,m0,2));
      m1=fmaxf(m1,__shfl_xor_sync(0xffffffffu,m1,1)); m1=fmaxf(m1,__shfl_xor_sync(0xffffffffu,m1,2));
      nb0=-(m0*SC+OFFS); nb1=-(m1*SC+OFFS); };
    newmax(S0);
    #pragma unroll
    for(int i=0;i<NF;i++) S0[i]=fmaf(S0[i],SC,((i>>1)&1)?nb1:nb0);
    auto step=[&](const int r, const int MODE, const int U, float (&S)[32], uint32_t (&P)[16], float (&Sn)[32], uint32_t (&Pp)[16]){
      const bool first=(U==0)&&MODE==1, second=(U==1)&&MODE==1, last=(U==1)&&MODE==2;
      if(second && r>0) epi(r-1);
      if(last){ if(r==1 || r==2) mbar_wait(B_Q+8*((r+1)&1),0); ldq(r+1); }
      const uint32_t vd= U==0 ? vd0+sp*(1024u-(1024u<<16))+4*(64u-(64u<<16)) : vd0+sc*(1024u-(1024u<<16));
      const uint32_t kd= U==0 ? kd0+sc*1024u+256u : kd0+sn*1024u;
      bool ok=true;
      const float c0=nb0, c1=nb1;
      auto ex=[&](const int i){ if(2*i>=NF) P[i]=pack(ex2(fmaf(S[2*i],SC,(i&1)?c1:c0)),ex2(fmaf(S[2*i+1],SC,(i&1)?c1:c0))); else P[i]=pack(ex2(S[2*i]),ex2(S[2*i+1])); };
      if(U==0 && !(MODE==2 && r==3)) ok=mbar_try(B_KF+8*sn, phn);
      wg_fence();
      qk(Sn,kd); wg_commit();
      #pragma unroll
      for(int kk=0;kk<4;kk++){
        if(second&&kk==0) wgmma_rs_n40z<1>(o,Pp[4*kk],Pp[4*kk+1],Pp[4*kk+2],Pp[4*kk+3],mk_desc2(vd+kk*(64u-(64u<<16)),HI64));
        else wgmma_rs_n40<1>(o,Pp[4*kk],Pp[4*kk+1],Pp[4*kk+2],Pp[4*kk+3],mk_desc2(vd+kk*(64u-(64u<<16)),HI64),1); }
      wg_commit();
      #pragma unroll
      for(int i=0;i<PA;i++) ex(i);
      #pragma unroll
      for(int i=0;i<PA;i++) asm volatile(""::"r"(P[i]));
      if(U==0){ if(__builtin_expect(!ok,0)) mbar_wait(B_KF+8*sn, phn); } else BOUND(1+MODE*8);
      #pragma unroll
      for(int i=PA;i<PART;i++) ex(i);
      #pragma unroll
      for(int i=PA;i<PART;i++) asm volatile(""::"r"(P[i]));
      BOUND(2+U+MODE*8);
      wg_wait<1>(); fence_regs(Sn);
      if(last) newmax(Sn);
      #pragma unroll
      for(int j=0;j<32;j++){
        if((j+1)*NF/32 != j*NF/32){ const int q=j*NF/32; Sn[q]=fmaf(Sn[q],SC,((q>>1)&1)?nb1:nb0); }
        if((j+1)*(16-PART)/32 != j*(16-PART)/32) ex(PART+j*(16-PART)/32); }
      fence_regs(Sn);
      #pragma unroll
      for(int i=PART;i<16;i++) asm volatile(""::"r"(P[i]));
      wg_wait<0>(); fence_regs(o);
      if(U==0){ if(l0 && !(first && r==0)) mbar_arrive(B_KE+8*sp);
      }
      else { sp=sc; sc=sn; sn=sn+1==NST?0:sn+1; phn^=(sn==0); }
    };
    #pragma unroll 1
    for(int r=0;r<4;r++){
      step(r,1,0,S0,P0,S1,P1); step(r,1,1,S1,P1,S0,P0);
      #pragma unroll 1
      for(int t=0;t<14;t++){ step(r,0,0,S0,P0,S1,P1); step(r,0,1,S1,P1,S0,P0); }
      step(r,2,0,S0,P0,S1,P1); step(r,2,1,S1,P1,S0,P0);
    }
    { const uint32_t vd=vd0+sp*(1024u-(1024u<<16))+4*(64u-(64u<<16));
      wg_fence();
      #pragma unroll
      for(int kk=0;kk<4;kk++) wgmma_rs_n40<1>(o,P1[4*kk],P1[4*kk+1],P1[4*kk+2],P1[4*kk+3],mk_desc2(vd+kk*(64u-(64u<<16)),HI64),1);
      wg_commit(); }
    wg_wait<0>(); fence_regs(o);
    epi(3);
  }
}

typedef CUresult (*PFN_enc)(CUtensorMap*, CUtensorMapDataType, cuuint32_t, void*, const cuuint64_t*, const cuuint64_t*, const cuuint32_t*, const cuuint32_t*, CUtensorMapInterleave, CUtensorMapSwizzle, CUtensorMapL2promotion, CUtensorMapFloatOOBfill);
static CUtensorMap mk_map(PFN_enc fn, const void* p, int rank, const cuuint64_t* dims, const cuuint64_t* strides, const cuuint32_t* box, CUtensorMapSwizzle sw){
  CUtensorMap m; cuuint32_t es[4]={1,1,1,1};
  fn(&m, CU_TENSOR_MAP_DATA_TYPE_BFLOAT16, rank, (void*)p, dims, strides, box, es, CU_TENSOR_MAP_INTERLEAVE_NONE, sw, CU_TENSOR_MAP_L2_PROMOTION_L2_256B, CU_TENSOR_MAP_FLOAT_OOB_FILL_NONE);
  return m; }
static CUtensorMap map2d(PFN_enc fn, const void* p, uint64_t inner, uint64_t outer, uint32_t bi, uint32_t bo, CUtensorMapSwizzle sw){
  cuuint64_t d[2]={inner,outer}, s[1]={inner*2}; cuuint32_t b[2]={bi,bo}; return mk_map(fn,p,2,d,s,b,sw); }

extern "C" void kernel_launch(void* const* d_in, const int* in_sizes, int n_in, void* d_out, int out_size){
  static bool init=false; static Maps mp; static const void* key[8];
  const void* cur[8]={d_in[0],d_in[1],d_in[2],d_in[3],d_in[5],d_in[6],d_in[7],d_out};
  bool same=init; for(int i=0;i<8;i++) same = same && key[i]==cur[i];
  if(!same){
    PFN_enc fn=nullptr; cudaDriverEntryPointQueryResult q; cudaGetDriverEntryPoint("cuTensorMapEncodeTiled",(void**)&fn,cudaEnableDefault,&q);
    void* go; cudaGetSymbolAddress(&go,g_o);
    const CUtensorMapSwizzle S128=CU_TENSOR_MAP_SWIZZLE_128B;
    mp.x=map2d(fn,d_in[0],1024,2048,64,128,S128);
    mp.wa=map2d(fn,d_in[1],3072,1024,64,64,S128);
    mp.wb=map2d(fn,d_in[5],3072,1024,64,64,S128);
    mp.go=map2d(fn,go,2048,2048,64,128,S128);
    mp.gos=map2d(fn,go,2048,2048,32,128,CU_TENSOR_MAP_SWIZZLE_64B);
    mp.woa=map2d(fn,d_in[3],1024,1024,64,64,S128);
    { cuuint64_t d[4]={1024,32,4,8}, s[3]={2048,65536,262144}; cuuint32_t b[4]={64,32,1,2}; mp.wob=mk_map(fn,d_in[6],4,d,s,b,S128); }
    mp.out=map2d(fn,d_out,1024,2048,64,128,S128);
    mp.wphi=map2d(fn,d_in[2],32,1024,32,128,CU_TENSOR_MAP_SWIZZLE_64B);
    mp.xp=(const bf16*)d_in[0]; mp.gw=(const bf16*)d_in[7];
    cudaFuncSetAttribute(k_main,cudaFuncAttributeMaxDynamicSharedMemorySize,k2::SMEM);
    for(int i=0;i<8;i++) key[i]=cur[i];
    init=true;
  }
  cudaLaunchConfig_t cfg={}; cfg.gridDim=128; cfg.blockDim=512; cfg.dynamicSmemBytes=k2::SMEM; cfg.stream=cudaStreamPerThread;
  cudaLaunchAttribute at[1];
  at[0].id=cudaLaunchAttributeClusterDimension; at[0].val.clusterDim.x=2; at[0].val.clusterDim.y=1; at[0].val.clusterDim.z=1;
  cfg.attrs=at; cfg.numAttrs=1;
  cudaLaunchKernelEx(&cfg,k_main,mp);
}
```

```cpp
#include <cuda_runtime.h>
#include <cuda_bf16.h>
#include <cuda.h>
#include <stdint.h>

typedef __nv_bfloat16 bf16;
#define DEVI __device__ __forceinline__

DEVI uint32_t smem_u32(const void* p){ return (uint32_t)__cvta_generic_to_shared(p); }
DEVI void mbar_init(uint32_t bar, uint32_t cnt){ asm volatile("mbarrier.init.shared::cta.b64 [%0], %1;"::"r"(bar),"r"(cnt):"memory"); }
DEVI void mbar_expect_tx(uint32_t bar, uint32_t bytes){ asm volatile("mbarrier.arrive.expect_tx.shared::cta.b64 _, [%0], %1;"::"r"(bar),"r"(bytes):"memory"); }
DEVI void mbar_arrive(uint32_t bar){ asm volatile("mbarrier.arrive.shared::cta.b64 _, [%0];"::"r"(bar):"memory"); }
DEVI bool mbar_try(uint32_t bar, uint32_t parity){ uint32_t ok;
  asm volatile("{\n.reg .pred p;\nmbarrier.try_wait.parity.shared::cta.b64 p, [%1], %2;\nselp.u32 %0, 1, 0, p;\n}\n":"=r"(ok):"r"(bar),"r"(parity):"memory"); return ok; }
DEVI void mbar_wait(uint32_t bar, uint32_t parity){
  asm volatile("{\n.reg .pred p;\n.reg .u32 c;\nmov.u32 c, 0;\nLAB_WAIT:\nmbarrier.try_wait.parity.shared::cta.b64 p, [%0], %1;\n@p bra DONE;\nadd.u32 c, c, 1;\nsetp.lt.u32 p, c, 0x200000;\n@p bra LAB_WAIT;\ntrap;\nDONE:\n}\n"::"r"(bar),"r"(parity):"memory"); }
DEVI void tma2d(uint32_t dst, const CUtensorMap* m, int c0, int c1, uint32_t bar){
  asm volatile("cp.async.bulk.tensor.2d.shared::cluster.global.mbarrier::complete_tx::bytes [%0], [%1, {%3, %4}], [%2];"::"r"(dst),"l"(m),"r"(bar),"r"(c0),"r"(c1):"memory"); }
DEVI void tma2d_mc(uint32_t dst, const CUtensorMap* m, int c0, int c1, uint32_t bar, uint16_t mask){
  asm volatile("cp.async.bulk.tensor.2d.shared::cluster.global.mbarrier::complete_tx::bytes.multicast::cluster [%0], [%1, {%3, %4}], [%2], %5;"::"r"(dst),"l"(m),"r"(bar),"r"(c0),"r"(c1),"h"(mask):"memory"); }
DEVI void tma3d_mc(uint32_t dst, const CUtensorMap* m, int c0, int c1, int c2, uint32_t bar, uint16_t mask){
  asm volatile("cp.async.bulk.tensor.3d.shared::cluster.global.mbarrier::complete_tx::bytes.multicast::cluster [%0], [%1, {%3, %4, %5}], [%2], %6;"::"r"(dst),"l"(m),"r"(bar),"r"(c0),"r"(c1),"r"(c2),"h"(mask):"memory"); }
DEVI void tma4d_mc(uint32_t dst, const CUtensorMap* m, int c0, int c1, int c2, int c3, uint32_t bar, uint16_t mask){
  asm volatile("cp.async.bulk.tensor.4d.shared::cluster.global.mbarrier::complete_tx::bytes.multicast::cluster [%0], [%1, {%3, %4, %5, %6}], [%2], %7;"::"r"(dst),"l"(m),"r"(bar),"r"(c0),"r"(c1),"r"(c2),"r"(c3),"h"(mask):"memory"); }
DEVI void tma4d(uint32_t dst, const CUtensorMap* m, int c0, int c1, int c2, int c3, uint32_t bar){
  asm volatile("cp.async.bulk.tensor.4d.shared::cluster.global.mbarrier::complete_tx::bytes [%0], [%1, {%3, %4, %5, %6}], [%2];"::"r"(dst),"l"(m),"r"(bar),"r"(c0),"r"(c1),"r"(c2),"r"(c3):"memory"); }
DEVI uint32_t mapa(uint32_t a, uint32_t rank){ uint32_t r; asm("mapa.shared::cluster.u32 %0, %1, %2;":"=r"(r):"r"(a),"r"(rank)); return r; }
DEVI void mbar_arrive_cl(uint32_t a){ asm volatile("mbarrier.arrive.shared::cluster.b64 _, [%0];"::"r"(a):"memory"); }
DEVI void cluster_sync(){ asm volatile("barrier.cluster.arrive.relaxed.aligned;\nbarrier.cluster.wait.acquire.aligned;":::"memory"); }
DEVI void tma3d(uint32_t dst, const CUtensorMap* m, int c0, int c1, int c2, uint32_t bar){
  asm volatile("cp.async.bulk.tensor.3d.shared::cluster.global.mbarrier::complete_tx::bytes [%0], [%1, {%3, %4, %5}], [%2];"::"r"(dst),"l"(m),"r"(bar),"r"(c0),"r"(c1),"r"(c2):"memory"); }
DEVI void tma2d_store(const CUtensorMap* m, uint32_t src, int c0, int c1){
  asm volatile("cp.async.bulk.tensor.2d.global.shared::cta.bulk_group [%0, {%2, %3}], [%1];"::"l"(m),"r"(src),"r"(c0),"r"(c1):"memory"); }
DEVI void bulk_g2s(uint32_t dst, const void* src, uint32_t bytes, uint32_t bar){
  asm volatile("cp.async.bulk.shared::cluster.global.mbarrier::complete_tx::bytes [%0], [%1], %2, [%3];"::"r"(dst),"l"(src),"r"(bytes),"r"(bar):"memory"); }
DEVI void bulk_s2g(void* dst, uint32_t src, uint32_t bytes){
  asm volatile("cp.async.bulk.global.shared::cta.bulk_group [%0], [%1], %2;"::"l"(dst),"r"(src),"r"(bytes):"memory"); }
DEVI void bulk_commit(){ asm volatile("cp.async.bulk.commit_group;":::"memory"); }
template<int N> DEVI void bulk_wait(){ asm volatile("cp.async.bulk.wait_group %0;"::"n"(N):"memory"); }
template<int N> DEVI void bulk_wait_read(){ asm volatile("cp.async.bulk.wait_group.read %0;"::"n"(N):"memory"); }
DEVI void fence_async_smem(){ asm volatile("fence.proxy.async.shared::cta;":::"memory"); }
DEVI void fence_async_all(){ asm volatile("fence.proxy.async.global;":::"memory"); }
DEVI void wg_fence(){ asm volatile("wgmma.fence.sync.aligned;":::"memory"); }
DEVI void wg_commit(){ asm volatile("wgmma.commit_group.sync.aligned;":::"memory"); }
template<int N> DEVI void wg_wait(){ asm volatile("wgmma.wait_group.sync.aligned %0;"::"n"(N):"memory"); }
DEVI uint64_t mk_desc2(uint32_t lo, uint32_t hi){ uint64_t d; asm("mov.b64 %0, {%1,%2};":"=l"(d):"r"(lo),"r"(hi)); return d; }
template<int R> DEVI void reg_alloc(){ asm volatile("setmaxnreg.inc.sync.aligned.u32 %0;"::"n"(R)); }
template<int R> DEVI void reg_dealloc(){ asm volatile("setmaxnreg.dec.sync.aligned.u32 %0;"::"n"(R)); }
template<int N> DEVI void fence_regs(float (&r)[N]){
  #pragma unroll
  for(int i=0;i<N;i++) asm volatile("":"+f"(r[i])::"memory"); }
DEVI void griddep_wait(){ asm volatile("griddepcontrol.wait;":::"memory"); }
DEVI void bar_sync(int id, int n){ asm volatile("bar.sync %0, %1;"::"r"(id),"r"(n):"memory"); }
DEVI void bar_arrive(int id, int n){ asm volatile("bar.arrive %0, %1;"::"r"(id),"r"(n):"memory"); }
DEVI float ex2(float x){ float y; asm("ex2.approx.ftz.f32 %0,%1;":"=f"(y):"f"(x)); return y; }
DEVI float rcp(float x){ float y; asm("rcp.approx.ftz.f32 %0,%1;":"=f"(y):"f"(x)); return y; }
DEVI uint32_t pack(float lo,float hi){ uint32_t y; asm("cvt.rn.bf16x2.f32 %0,%1,%2;":"=r"(y):"f"(hi),"f"(lo)); return y; }
DEVI void stsm4(uint32_t a, uint32_t r0, uint32_t r1, uint32_t r2, uint32_t r3){
  asm volatile("stmatrix.sync.aligned.m8n8.x4.shared.b16 [%0], {%1,%2,%3,%4};"::"r"(a),"r"(r0),"r"(r1),"r"(r2),"r"(r3):"memory"); }
DEVI void flag_add(unsigned* p){ asm volatile("fence.acq_rel.gpu;\nred.relaxed.gpu.global.add.u32 [%0], 1;"::"l"(p):"memory"); }
DEVI unsigned ld_acq(const unsigned* p){ unsigned v; asm volatile("ld.acquire.gpu.global.u32 %0, [%1];":"=r"(v):"l"(p):"memory"); return v; }
DEVI void flag_set(unsigned* p, unsigned v){ asm volatile("st.release.gpu.global.u32 [%0], %1;"::"l"(p),"r"(v):"memory"); }
DEVI void flag_set_rlx(unsigned* p, unsigned v){ asm volatile("fence.proxy.async.global;\nst.relaxed.gpu.global.u32 [%0], %1;"::"l"(p),"r"(v):"memory"); }
DEVI void flag_add_rlx(unsigned* p){ asm volatile("fence.proxy.async.global;\nred.relaxed.gpu.global.add.u32 [%0], 1;"::"l"(p):"memory"); }
DEVI void flag_wait(const unsigned* p, unsigned target){
  for(int i=0;i<(1<<22);i++){ if((int)(ld_acq(p)-target)>=0) return; __nanosleep(40); }
  asm volatile("trap;"); }
DEVI void flag_wait_eq(const unsigned* p, unsigned tag){
  for(int i=0;i<(1<<22);i++){ if(ld_acq(p)==tag) return; __nanosleep(40); }
  asm volatile("trap;"); }
DEVI void red2(float* p, float a, float b){ asm volatile("red.relaxed.gpu.global.add.v2.f32 [%0], {%1,%2};"::"l"(p),"f"(a),"f"(b):"memory"); }
DEVI void red1(float* p, float a){ asm volatile("red.relaxed.gpu.global.add.f32 [%0], %1;"::"l"(p),"f"(a):"memory"); }
#define BOUND(c) asm volatile("{\n.reg .pred p;\nsetp.eq.u32 p, %0, %1;\n@p exit;\n}\n"::"r"(zz),"r"(c):"memory")
template<int TB> DEVI void wgmma_rs_n128(float (&d)[64], uint32_t a0, uint32_t a1, uint32_t a2, uint32_t a3, uint64_t db, int sd){
  asm volatile("{\n.reg .pred p;\nsetp.ne.b32 p, %69, 0;\n"
    "wgmma.mma_async.sync.aligned.m64n128k16.f32.bf16.bf16 {%0, %1, %2, %3, %4, %5, %6, %7, %8, %9, %10, %11, %12, %13, %14, %15, %16, %17, %18, %19, %20, %21, %22, %23, %24, %25, %26, %27, %28, %29, %30, %31, %32, %33, %34, %35, %36, %37, %38, %39, %40, %41, %42, %43, %44, %45, %46, %47, %48, %49, %50, %51, %52, %53, %54, %55, %56, %57, %58, %59, %60, %61, %62, %63}, {%64,%65,%66,%67}, %68, p, 1, 1, %70;\n}\n"
    : "+f"(d[0]), "+f"(d[1]), "+f"(d[2]), "+f"(d[3]), "+f"(d[4]), "+f"(d[5]), "+f"(d[6]), "+f"(d[7]), "+f"(d[8]), "+f"(d[9]), "+f"(d[10]), "+f"(d[11]), "+f"(d[12]), "+f"(d[13]), "+f"(d[14]), "+f"(d[15]), "+f"(d[16]), "+f"(d[17]), "+f"(d[18]), "+f"(d[19]), "+f"(d[20]), "+f"(d[21]), "+f"(d[22]), "+f"(d[23]), "+f"(d[24]), "+f"(d[25]), "+f"(d[26]), "+f"(d[27]), "+f"(d[28]), "+f"(d[29]), "+f"(d[30]), "+f"(d[31]), "+f"(d[32]), "+f"(d[33]), "+f"(d[34]), "+f"(d[35]), "+f"(d[36]), "+f"(d[37]), "+f"(d[38]), "+f"(d[39]), "+f"(d[40]), "+f"(d[41]), "+f"(d[42]), "+f"(d[43]), "+f"(d[44]), "+f"(d[45]), "+f"(d[46]), "+f"(d[47]), "+f"(d[48]), "+f"(d[49]), "+f"(d[50]), "+f"(d[51]), "+f"(d[52]), "+f"(d[53]), "+f"(d[54]), "+f"(d[55]), "+f"(d[56]), "+f"(d[57]), "+f"(d[58]), "+f"(d[59]), "+f"(d[60]), "+f"(d[61]), "+f"(d[62]), "+f"(d[63])
    : "r"(a0), "r"(a1), "r"(a2), "r"(a3), "l"(db), "r"(sd), "n"(TB));
}
template<int TB> DEVI void wgmma_rs_n128z(float (&d)[64], uint32_t a0, uint32_t a1, uint32_t a2, uint32_t a3, uint64_t db){
  asm volatile("{\n.reg .pred p;\nsetp.ne.b32 p, 0, 0;\n"
    "wgmma.mma_async.sync.aligned.m64n128k16.f32.bf16.bf16 {%0, %1, %2, %3, %4, %5, %6, %7, %8, %9, %10, %11, %12, %13, %14, %15, %16, %17, %18, %19, %20, %21, %22, %23, %24, %25, %26, %27, %28, %29, %30, %31, %32, %33, %34, %35, %36, %37, %38, %39, %40, %41, %42, %43, %44, %45, %46, %47, %48, %49, %50, %51, %52, %53, %54, %55, %56, %57, %58, %59, %60, %61, %62, %63}, {%64,%65,%66,%67}, %68, p, 1, 1, %69;\n}\n"
    : "=f"(d[0]), "=f"(d[1]), "=f"(d[2]), "=f"(d[3]), "=f"(d[4]), "=f"(d[5]), "=f"(d[6]), "=f"(d[7]), "=f"(d[8]), "=f"(d[9]), "=f"(d[10]), "=f"(d[11]), "=f"(d[12]), "=f"(d[13]), "=f"(d[14]), "=f"(d[15]), "=f"(d[16]), "=f"(d[17]), "=f"(d[18]), "=f"(d[19]), "=f"(d[20]), "=f"(d[21]), "=f"(d[22]), "=f"(d[23]), "=f"(d[24]), "=f"(d[25]), "=f"(d[26]), "=f"(d[27]), "=f"(d[28]), "=f"(d[29]), "=f"(d[30]), "=f"(d[31]), "=f"(d[32]), "=f"(d[33]), "=f"(d[34]), "=f"(d[35]), "=f"(d[36]), "=f"(d[37]), "=f"(d[38]), "=f"(d[39]), "=f"(d[40]), "=f"(d[41]), "=f"(d[42]), "=f"(d[43]), "=f"(d[44]), "=f"(d[45]), "=f"(d[46]), "=f"(d[47]), "=f"(d[48]), "=f"(d[49]), "=f"(d[50]), "=f"(d[51]), "=f"(d[52]), "=f"(d[53]), "=f"(d[54]), "=f"(d[55]), "=f"(d[56]), "=f"(d[57]), "=f"(d[58]), "=f"(d[59]), "=f"(d[60]), "=f"(d[61]), "=f"(d[62]), "=f"(d[63])
    : "r"(a0), "r"(a1), "r"(a2), "r"(a3), "l"(db), "n"(TB));
}
template<int TA, int TB> DEVI void wgmma_ss_n128(float (&d)[64], uint64_t da, uint64_t db, int sd){
  asm volatile("{\n.reg .pred p;\nsetp.ne.b32 p, %66, 0;\n"
    "wgmma.mma_async.sync.aligned.m64n128k16.f32.bf16.bf16 {%0, %1, %2, %3, %4, %5, %6, %7, %8, %9, %10, %11, %12, %13, %14, %15, %16, %17, %18, %19, %20, %21, %22, %23, %24, %25, %26, %27, %28, %29, %30, %31, %32, %33, %34, %35, %36, %37, %38, %39, %40, %41, %42, %43, %44, %45, %46, %47, %48, %49, %50, %51, %52, %53, %54, %55, %56, %57, %58, %59, %60, %61, %62, %63}, %64, %65, p, 1, 1, %67, %68;\n}\n"
    : "+f"(d[0]), "+f"(d[1]), "+f"(d[2]), "+f"(d[3]), "+f"(d[4]), "+f"(d[5]), "+f"(d[6]), "+f"(d[7]), "+f"(d[8]), "+f"(d[9]), "+f"(d[10]), "+f"(d[11]), "+f"(d[12]), "+f"(d[13]), "+f"(d[14]), "+f"(d[15]), "+f"(d[16]), "+f"(d[17]), "+f"(d[18]), "+f"(d[19]), "+f"(d[20]), "+f"(d[21]), "+f"(d[22]), "+f"(d[23]), "+f"(d[24]), "+f"(d[25]), "+f"(d[26]), "+f"(d[27]), "+f"(d[28]), "+f"(d[29]), "+f"(d[30]), "+f"(d[31]), "+f"(d[32]), "+f"(d[33]), "+f"(d[34]), "+f"(d[35]), "+f"(d[36]), "+f"(d[37]), "+f"(d[38]), "+f"(d[39]), "+f"(d[40]), "+f"(d[41]), "+f"(d[42]), "+f"(d[43]), "+f"(d[44]), "+f"(d[45]), "+f"(d[46]), "+f"(d[47]), "+f"(d[48]), "+f"(d[49]), "+f"(d[50]), "+f"(d[51]), "+f"(d[52]), "+f"(d[53]), "+f"(d[54]), "+f"(d[55]), "+f"(d[56]), "+f"(d[57]), "+f"(d[58]), "+f"(d[59]), "+f"(d[60]), "+f"(d[61]), "+f"(d[62]), "+f"(d[63])
    : "l"(da), "l"(db), "r"(sd), "n"(TA), "n"(TB));
}
template<int TA, int TB> DEVI void wgmma_ss_n128z(float (&d)[64], uint64_t da, uint64_t db){
  asm volatile("{\n.reg .pred p;\nsetp.ne.b32 p, 0, 0;\n"
    "wgmma.mma_async.sync.aligned.m64n128k16.f32.bf16.bf16 {%0, %1, %2, %3, %4, %5, %6, %7, %8, %9, %10, %11, %12, %13, %14, %15, %16, %17, %18, %19, %20, %21, %22, %23, %24, %25, %26, %27, %28, %29, %30, %31, %32, %33, %34, %35, %36, %37, %38, %39, %40, %41, %42, %43, %44, %45, %46, %47, %48, %49, %50, %51, %52, %53, %54, %55, %56, %57, %58, %59, %60, %61, %62, %63}, %64, %65, p, 1, 1, %66, %67;\n}\n"
    : "=f"(d[0]), "=f"(d[1]), "=f"(d[2]), "=f"(d[3]), "=f"(d[4]), "=f"(d[5]), "=f"(d[6]), "=f"(d[7]), "=f"(d[8]), "=f"(d[9]), "=f"(d[10]), "=f"(d[11]), "=f"(d[12]), "=f"(d[13]), "=f"(d[14]), "=f"(d[15]), "=f"(d[16]), "=f"(d[17]), "=f"(d[18]), "=f"(d[19]), "=f"(d[20]), "=f"(d[21]), "=f"(d[22]), "=f"(d[23]), "=f"(d[24]), "=f"(d[25]), "=f"(d[26]), "=f"(d[27]), "=f"(d[28]), "=f"(d[29]), "=f"(d[30]), "=f"(d[31]), "=f"(d[32]), "=f"(d[33]), "=f"(d[34]), "=f"(d[35]), "=f"(d[36]), "=f"(d[37]), "=f"(d[38]), "=f"(d[39]), "=f"(d[40]), "=f"(d[41]), "=f"(d[42]), "=f"(d[43]), "=f"(d[44]), "=f"(d[45]), "=f"(d[46]), "=f"(d[47]), "=f"(d[48]), "=f"(d[49]), "=f"(d[50]), "=f"(d[51]), "=f"(d[52]), "=f"(d[53]), "=f"(d[54]), "=f"(d[55]), "=f"(d[56]), "=f"(d[57]), "=f"(d[58]), "=f"(d[59]), "=f"(d[60]), "=f"(d[61]), "=f"(d[62]), "=f"(d[63])
    : "l"(da), "l"(db), "n"(TA), "n"(TB));
}
template<int TB> DEVI void wgmma_rs_n40(float (&d)[20], uint32_t a0, uint32_t a1, uint32_t a2, uint32_t a3, uint64_t db, int sd){
  asm volatile("{\n.reg .pred p;\nsetp.ne.b32 p, %25, 0;\n"
    "wgmma.mma_async.sync.aligned.m64n40k16.f32.bf16.bf16 {%0, %1, %2, %3, %4, %5, %6, %7, %8, %9, %10, %11, %12, %13, %14, %15, %16, %17, %18, %19}, {%20,%21,%22,%23}, %24, p, 1, 1, %26;\n}\n"
    : "+f"(d[0]), "+f"(d[1]), "+f"(d[2]), "+f"(d[3]), "+f"(d[4]), "+f"(d[5]), "+f"(d[6]), "+f"(d[7]), "+f"(d[8]), "+f"(d[9]), "+f"(d[10]), "+f"(d[11]), "+f"(d[12]), "+f"(d[13]), "+f"(d[14]), "+f"(d[15]), "+f"(d[16]), "+f"(d[17]), "+f"(d[18]), "+f"(d[19])
    : "r"(a0), "r"(a1), "r"(a2), "r"(a3), "l"(db), "r"(sd), "n"(TB));
}
template<int TB> DEVI void wgmma_rs_n40z(float (&d)[20], uint32_t a0, uint32_t a1, uint32_t a2, uint32_t a3, uint64_t db){
  asm volatile("{\n.reg .pred p;\nsetp.ne.b32 p, 0, 0;\n"
    "wgmma.mma_async.sync.aligned.m64n40k16.f32.bf16.bf16 {%0, %1, %2, %3, %4, %5, %6, %7, %8, %9, %10, %11, %12, %13, %14, %15, %16, %17, %18, %19}, {%20,%21,%22,%23}, %24, p, 1, 1, %25;\n}\n"
    : "=f"(d[0]), "=f"(d[1]), "=f"(d[2]), "=f"(d[3]), "=f"(d[4]), "=f"(d[5]), "=f"(d[6]), "=f"(d[7]), "=f"(d[8]), "=f"(d[9]), "=f"(d[10]), "=f"(d[11]), "=f"(d[12]), "=f"(d[13]), "=f"(d[14]), "=f"(d[15]), "=f"(d[16]), "=f"(d[17]), "=f"(d[18]), "=f"(d[19])
    : "r"(a0), "r"(a1), "r"(a2), "r"(a3), "l"(db), "n"(TB));
}
template<int TA, int TB> DEVI void wgmma_ss_n40(float (&d)[20], uint64_t da, uint64_t db, int sd){
  asm volatile("{\n.reg .pred p;\nsetp.ne.b32 p, %22, 0;\n"
    "wgmma.mma_async.sync.aligned.m64n40k16.f32.bf16.bf16 {%0, %1, %2, %3, %4, %5, %6, %7, %8, %9, %10, %11, %12, %13, %14, %15, %16, %17, %18, %19}, %20, %21, p, 1, 1, %23, %24;\n}\n"
    : "+f"(d[0]), "+f"(d[1]), "+f"(d[2]), "+f"(d[3]), "+f"(d[4]), "+f"(d[5]), "+f"(d[6]), "+f"(d[7]), "+f"(d[8]), "+f"(d[9]), "+f"(d[10]), "+f"(d[11]), "+f"(d[12]), "+f"(d[13]), "+f"(d[14]), "+f"(d[15]), "+f"(d[16]), "+f"(d[17]), "+f"(d[18]), "+f"(d[19])
    : "l"(da), "l"(db), "r"(sd), "n"(TA), "n"(TB));
}
template<int TA, int TB> DEVI void wgmma_ss_n40z(float (&d)[20], uint64_t da, uint64_t db){
  asm volatile("{\n.reg .pred p;\nsetp.ne.b32 p, 0, 0;\n"
    "wgmma.mma_async.sync.aligned.m64n40k16.f32.bf16.bf16 {%0, %1, %2, %3, %4, %5, %6, %7, %8, %9, %10, %11, %12, %13, %14, %15, %16, %17, %18, %19}, %20, %21, p, 1, 1, %22, %23;\n}\n"
    : "=f"(d[0]), "=f"(d[1]), "=f"(d[2]), "=f"(d[3]), "=f"(d[4]), "=f"(d[5]), "=f"(d[6]), "=f"(d[7]), "=f"(d[8]), "=f"(d[9]), "=f"(d[10]), "=f"(d[11]), "=f"(d[12]), "=f"(d[13]), "=f"(d[14]), "=f"(d[15]), "=f"(d[16]), "=f"(d[17]), "=f"(d[18]), "=f"(d[19])
    : "l"(da), "l"(db), "n"(TA), "n"(TB));
}
template<int TB> DEVI void wgmma_rs_n32(float (&d)[16], uint32_t a0, uint32_t a1, uint32_t a2, uint32_t a3, uint64_t db, int sd){
  asm volatile("{\n.reg .pred p;\nsetp.ne.b32 p, %21, 0;\n"
    "wgmma.mma_async.sync.aligned.m64n32k16.f32.bf16.bf16 {%0, %1, %2, %3, %4, %5, %6, %7, %8, %9, %10, %11, %12, %13, %14, %15}, {%16,%17,%18,%19}, %20, p, 1, 1, %22;\n}\n"
    : "+f"(d[0]), "+f"(d[1]), "+f"(d[2]), "+f"(d[3]), "+f"(d[4]), "+f"(d[5]), "+f"(d[6]), "+f"(d[7]), "+f"(d[8]), "+f"(d[9]), "+f"(d[10]), "+f"(d[11]), "+f"(d[12]), "+f"(d[13]), "+f"(d[14]), "+f"(d[15])
    : "r"(a0), "r"(a1), "r"(a2), "r"(a3), "l"(db), "r"(sd), "n"(TB));
}
template<int TB> DEVI void wgmma_rs_n32z(float (&d)[16], uint32_t a0, uint32_t a1, uint32_t a2, uint32_t a3, uint64_t db){
  asm volatile("{\n.reg .pred p;\nsetp.ne.b32 p, 0, 0;\n"
    "wgmma.mma_async.sync.aligned.m64n32k16.f32.bf16.bf16 {%0, %1, %2, %3, %4, %5, %6, %7, %8, %9, %10, %11, %12, %13, %14, %15}, {%16,%17,%18,%19}, %20, p, 1, 1, %21;\n}\n"
    : "=f"(d[0]), "=f"(d[1]), "=f"(d[2]), "=f"(d[3]), "=f"(d[4]), "=f"(d[5]), "=f"(d[6]), "=f"(d[7]), "=f"(d[8]), "=f"(d[9]), "=f"(d[10]), "=f"(d[11]), "=f"(d[12]), "=f"(d[13]), "=f"(d[14]), "=f"(d[15])
    : "r"(a0), "r"(a1), "r"(a2), "r"(a3), "l"(db), "n"(TB));
}
template<int TB> DEVI void wgmma_rs_n64(float (&d)[32], uint32_t a0, uint32_t a1, uint32_t a2, uint32_t a3, uint64_t db, int sd){
  asm volatile("{\n.reg .pred p;\nsetp.ne.b32 p, %37, 0;\n"
    "wgmma.mma_async.sync.aligned.m64n64k16.f32.bf16.bf16 {%0, %1, %2, %3, %4, %5, %6, %7, %8, %9, %10, %11, %12, %13, %14, %15, %16, %17, %18, %19, %20, %21, %22, %23, %24, %25, %26, %27, %28, %29, %30, %31}, {%32,%33,%34,%35}, %36, p, 1, 1, %38;\n}\n"
    : "+f"(d[0]), "+f"(d[1]), "+f"(d[2]), "+f"(d[3]), "+f"(d[4]), "+f"(d[5]), "+f"(d[6]), "+f"(d[7]), "+f"(d[8]), "+f"(d[9]), "+f"(d[10]), "+f"(d[11]), "+f"(d[12]), "+f"(d[13]), "+f"(d[14]), "+f"(d[15]), "+f"(d[16]), "+f"(d[17]), "+f"(d[18]), "+f"(d[19]), "+f"(d[20]), "+f"(d[21]), "+f"(d[22]), "+f"(d[23]), "+f"(d[24]), "+f"(d[25]), "+f"(d[26]), "+f"(d[27]), "+f"(d[28]), "+f"(d[29]), "+f"(d[30]), "+f"(d[31])
    : "r"(a0), "r"(a1), "r"(a2), "r"(a3), "l"(db), "r"(sd), "n"(TB));
}
template<int TB> DEVI void wgmma_rs_n64z(float (&d)[32], uint32_t a0, uint32_t a1, uint32_t a2, uint32_t a3, uint64_t db){
  asm volatile("{\n.reg .pred p;\nsetp.ne.b32 p, 0, 0;\n"
    "wgmma.mma_async.sync.aligned.m64n64k16.f32.bf16.bf16 {%0, %1, %2, %3, %4, %5, %6, %7, %8, %9, %10, %11, %12, %13, %14, %15, %16, %17, %18, %19, %20, %21, %22, %23, %24, %25, %26, %27, %28, %29, %30, %31}, {%32,%33,%34,%35}, %36, p, 1, 1, %37;\n}\n"
    : "=f"(d[0]), "=f"(d[1]), "=f"(d[2]), "=f"(d[3]), "=f"(d[4]), "=f"(d[5]), "=f"(d[6]), "=f"(d[7]), "=f"(d[8]), "=f"(d[9]), "=f"(d[10]), "=f"(d[11]), "=f"(d[12]), "=f"(d[13]), "=f"(d[14]), "=f"(d[15]), "=f"(d[16]), "=f"(d[17]), "=f"(d[18]), "=f"(d[19]), "=f"(d[20]), "=f"(d[21]), "=f"(d[22]), "=f"(d[23]), "=f"(d[24]), "=f"(d[25]), "=f"(d[26]), "=f"(d[27]), "=f"(d[28]), "=f"(d[29]), "=f"(d[30]), "=f"(d[31])
    : "r"(a0), "r"(a1), "r"(a2), "r"(a3), "l"(db), "n"(TB));
}

__device__ __align__(1024) bf16 g_q[32*2048*32];
__device__ __align__(1024) bf16 g_kvb[32*16*2*128*32];
__device__ __align__(1024) bf16 g_o[2048*2048];
__device__ __align__(16) float g_kv[2*32*64*40];
__device__ __align__(1024) uint4 g_kvi[8*1280];
__device__ __align__(16) unsigned g_cnt[192];
__device__ unsigned g_tile[32*16];
__device__ unsigned g_epoch;
__device__ float g_gate[2048];
constexpr int C_KV=0, C_KI=8, C_OA=16, C_OB=32, C_G=96, C_OP=128;

constexpr float LOG2E = 1.4426950408889634f;
constexpr float SC = 0.17677669529663687f*LOG2E;
constexpr float OFFS = 88.f;
constexpr uint32_t HI64 = (512u>>4)|(2u<<30);
constexpr uint32_t HI128 = (1024u>>4)|(1u<<30);
constexpr uint32_t SB = 1024;

#define RAV 144
#define RGV 200
#define PAV 3
#define PARTV 12
#define NF 32
#define NPRE 2
#define THR 3
#define NSL 100
#define EARLY 1
#define GCG 1
#define GW 1
namespace k2 {
  constexpr int NST=4, GST=4;
  constexpr uint32_t SQ=SB, SKV=SQ+16384, SG=SKV+NST*16384, SW=SG+GST*32768, SO=SW+8192, SONES=SO+8192, SGATE=SONES+1024, BARS=SGATE+512;
  constexpr uint32_t B_KF=BARS, B_KE=BARS+32, B_Q=BARS+64, B_W=BARS+80, B_GF=BARS+128, B_GE=BARS+192, B_PF=BARS+256, B_PE=BARS+320, B_E=BARS+96, B_X=BARS+104, B_O=BARS+112, SEP=BARS+384;
  constexpr uint32_t PST=49152, PR=SQ;
  constexpr uint32_t SMEM=BARS+512-SB;
  constexpr int RA=RAV, RG=RGV, RP=512-2*RAV-RGV;
  constexpr int PA=PAV, PART=PARTV;
}
struct Maps { CUtensorMap x, wa, go, gos, woa, wob, out, wphi, wb; const bf16 *xp, *gw; };

DEVI void mnmx(const float (&p)[16], float& x0, float& x1, float& n0, float& n1){
  x0=fmaxf(p[0],p[1]); n0=fminf(p[0],p[1]); x1=fmaxf(p[2],p[3]); n1=fminf(p[2],p[3]);
  #pragma unroll
  for(int j=1;j<4;j++){ x0=fmaxf(x0,fmaxf(p[4*j],p[4*j+1])); n0=fminf(n0,fminf(p[4*j],p[4*j+1])); x1=fmaxf(x1,fmaxf(p[4*j+2],p[4*j+3])); n1=fminf(n1,fminf(p[4*j+2],p[4*j+3])); }
  #pragma unroll
  for(int o=1;o<4;o<<=1){ x0=fmaxf(x0,__shfl_xor_sync(0xffffffffu,x0,o)); x1=fmaxf(x1,__shfl_xor_sync(0xffffffffu,x1,o));
                          n0=fminf(n0,__shfl_xor_sync(0xffffffffu,n0,o)); n1=fminf(n1,__shfl_xor_sync(0xffffffffu,n1,o)); }
}

__global__ void __launch_bounds__(512,1) k_main(const __grid_constant__ Maps mp){
  using namespace k2;
  extern __shared__ __align__(1024) uint8_t smem_raw[];
  const uint32_t cb=smem_u32(smem_raw)-SB;
  if(cb&0xffffffu) asm volatile("trap;");
  const uint32_t B_KF=cb+k2::B_KF, B_KE=cb+k2::B_KE, B_Q=cb+k2::B_Q, B_W=cb+k2::B_W, B_GF=cb+k2::B_GF, B_GE=cb+k2::B_GE, SGATE=cb+k2::SGATE,
                 B_PF=cb+k2::B_PF, B_PE=cb+k2::B_PE, B_E=cb+k2::B_E, B_X=cb+k2::B_X, B_O=cb+k2::B_O, SEP=cb+k2::SEP;
  const int tid=threadIdx.x, lane=tid&31, warp=__shfl_sync(0xffffffffu,tid>>5,0);
  const int m=blockIdx.x&15, hh=blockIdx.x>>4;
  if(tid==0){
    for(int s=0;s<NST;s++){ mbar_init(B_KF+8*s,1); mbar_init(B_KE+8*s,8); }
    for(int s=0;s<GST;s++){ mbar_init(B_GF+8*s,1); mbar_init(B_GE+8*s,8); }
    mbar_init(B_E,1); mbar_init(B_X,1); mbar_init(B_O,1);
    mbar_init(B_Q,1); mbar_init(B_Q+8,1); mbar_init(B_W,1); mbar_init(B_W+8,1);
    asm volatile("fence.mbarrier_init.release.cluster;":::"memory"); }
  if(tid==416){
    for(int s=0;s<4;s++){ mbar_init(B_PF+8*s,1); mbar_init(B_PE+8*s,16); }
    asm volatile("fence.mbarrier_init.release.cluster;":::"memory"); fence_async_smem();
    for(int s=0;s<4;s++){ const uint32_t a=cb+PR+s*PST; mbar_expect_tx(B_PF+8*s,PST); tma2d(a,&mp.x,s*64,m*128,B_PF+8*s);
      if(s<NPRE) for(int b=0;b<4;b++) tma2d(a+16384+b*8192,&mp.wb,(b<3 ? b*1024 : 2112)+hh*128,s*64,B_PF+8*s); }
  }
  if(tid<256) asm volatile("st.shared.u32 [%0], %1;"::"r"(cb+SONES+tid*4),"r"(0x3F803F80u):"memory");
  cluster_sync();
  auto epoch=[&]{ mbar_wait(B_E,0); uint32_t e; asm volatile("ld.shared.u32 %0, [%1];":"=r"(e):"r"(SEP):"memory"); return e; };

  if(warp>=12){
    reg_dealloc<RP>();
    if(warp==12){
      const uint32_t tag=epoch();
      bar_sync(3,EARLY ? 288 : 320);
      if(lane==0){
        const uint32_t pr=(m&1)^1;
        mbar_arrive_cl(mapa(B_X,pr));
        mbar_arrive(B_KF); mbar_expect_tx(B_KF+8,16384);
        mbar_wait(B_X,0);
        asm volatile("cp.async.bulk.shared::cluster.shared::cta.mbarrier::complete_tx::bytes [%0], [%1], %2, [%3];"::"r"(mapa(cb+SKV+16384,pr)),"r"(cb+SKV),"r"(16384),"r"(mapa(B_KF+8,pr)):"memory");
        bulk_s2g(g_kvb+((size_t)(4*hh+1)*16+m)*8192, cb+SKV+3*16384, 16384);
        bulk_commit();
      }
      uint32_t ready=0;
      #pragma unroll 1
      for(int it=2;it<64;it++){ const int h=4*hh+(it>>4), t=(it+(m&14))&15, sl=it&3;
        if((it&15)==0) ready=0;
        if(!((ready>>t)&1)){
          for(int i=0;;i++){ unsigned v; asm volatile("ld.relaxed.gpu.global.u32 %0, [%1];":"=r"(v):"l"(&g_tile[h*16+(lane&15)]):"memory");
            ready=__ballot_sync(0xffffffffu, v==tag); if((ready>>t)&1) break; if(i>(1<<22)) asm volatile("trap;"); __nanosleep(NSL); }
          asm volatile("fence.acq_rel.cta;":::"memory"); fence_async_all();
          }
        if(lane==0){
          if(it==3) bulk_wait_read<0>();
          if(it==4){ flag_wait_eq(&g_tile[(4*hh)*16+m],tag);
            mbar_wait(B_KF+8,0); mbar_arrive_cl(mapa(B_X,(m&1)^1));
            mbar_wait(B_X,1); }
          mbar_wait(B_KE+8*sl,((it>>2)&1)^1); mbar_expect_tx(B_KF+8*sl,16384);
          bulk_g2s(cb+SKV+sl*16384, g_kvb+((size_t)h*16+t)*8192, 16384, B_KF+8*sl);
          if(it==THR){
            #pragma unroll
            for(int i=0;i<8;i++) mbar_arrive_cl(mapa(B_GE+24,i&1)); }
          if(it==9) flag_wait_eq(&g_tile[(4*hh)*16+(m^1)],tag);
          if(it==5){
            #pragma unroll
            for(int j=0;j<2;j++) bulk_s2g(g_kvb+((size_t)(4*hh+2+j)*16+m)*8192+4096, cb+SW+j*8192, 8192);
            bulk_commit(); }
          if(it==7){ bulk_wait<0>(); flag_set_rlx(&g_tile[(4*hh+1)*16+m],tag); mbar_expect_tx(B_W,8192); tma2d(cb+SW,&mp.wphi,0,hh*128,B_W); }
          if(it==16+NST || it==32+NST){ const int r=(it>>4)&1^1;
            flag_wait_eq(&g_tile[(h+1)*16+m],tag); fence_async_all();
            mbar_expect_tx(B_Q+8*r,8192); bulk_g2s(cb+SQ+r*8192, g_q+((size_t)(h+1)*2048+m*128)*32, 8192, B_Q+8*r); } }
        __syncwarp(); }
    } else if(warp==13){
      if(lane==0){
        const uint32_t rank=m&1;
        #pragma unroll 1
        for(int it=NPRE;it<16;it++){ const int s=it&3, k=it*64; const uint32_t a=cb+PR+s*PST, bar=B_PF+8*s;
          if(it>=4){ mbar_wait(B_PE+8*s,((it>>2)&1)^1); mbar_expect_tx(bar,PST); tma2d(a,&mp.x,k,m*128,bar); }
          tma2d_mc(a+16384+rank*16384,&mp.wb,rank*2048+hh*128,k,bar,3);
          tma2d_mc(a+24576+rank*16384,&mp.wb,(rank ? 2112 : 1024)+hh*128,k,bar,3); }
        const uint32_t tag=epoch();
        #pragma unroll 1
        for(int it=0;it<93;it++){
          const int s=it&3; const uint32_t a=cb+SG+s*32768, bar=B_GF+8*s;
          mbar_wait(B_GE+8*s,(it>>2)&1);
          if(it<64){
            const int job=it>>4, k=(it&15)*64, n = job==0 ? rank*1024+hh*128+64 : job<3 ? 1024+rank*1024+hh*128+(job-1)*64 : hh*128+rank*64;
            mbar_expect_tx(bar,32768); tma2d_mc(a+16384+rank*8192,job==0 ? &mp.wb : &mp.wa,n,k,bar,3); tma2d(a,&mp.x,k,m*128,bar);
          } else if(it==64){
            flag_wait(&g_cnt[C_KI+hh],16*tag); fence_async_all();
            mbar_expect_tx(bar,20480); bulk_g2s(a,g_kvi+hh*1280,20480,bar);
          } else {
            const int j=it-65, k = j<8 ? 1024+j*64 : j<24 ? (j-8)*64 : 1024+(j-16)*64;
            mbar_expect_tx(bar,32768);
            if(k<1024) tma2d_mc(a+16384+rank*8192,&mp.woa,hh*128+rank*64,k,bar,3);
            else tma4d_mc(a+16384+rank*8192,&mp.wob,hh*128+rank*64,0,(k-1024)>>8,(k&255)>>5,bar,3);
            if(k==0){ flag_wait(&g_cnt[C_OA+m],8*tag); fence_async_all(); }
            if(k>=1024 && (k&255)==0){ flag_wait(&g_cnt[C_OB+((k-1024)>>8)*16+m],8*tag); fence_async_all(); }
            tma2d(a,&mp.go,k,m*128,bar);
          } }
        uint32_t todo=15;
        #pragma unroll 1
        for(int it=93;it<97;it++){
          const int s=it&3; const uint32_t a=cb+SG+s*32768, bar=B_GF+8*s;
          mbar_wait(B_GE+8*s,(it>>2)&1);
          uint32_t rdy=0;
          for(int i=0;!rdy;i++){ uint32_t c0,c1,c2,c3;
            asm volatile("ld.relaxed.gpu.global.v4.u32 {%0,%1,%2,%3}, [%4];":"=r"(c0),"=r"(c1),"=r"(c2),"=r"(c3):"l"(&g_cnt[C_OP+4*m]):"memory");
            rdy=todo&((c0==2*tag)|(c1==2*tag)<<1|(c2==2*tag)<<2|(c3==2*tag)<<3);
            if(i>(1<<22)) asm volatile("trap;"); }
          const int p=__ffs(rdy)-1; todo&=~(1u<<p);
          asm volatile("fence.acq_rel.cta;":::"memory"); fence_async_all();
          mbar_expect_tx(bar,32768);
          tma2d(a,&mp.go,1792+p*64,m*128,bar);
          tma4d(a+16384,&mp.wob,hh*128,0,3,2*p,bar); tma4d(a+24576,&mp.wob,hh*128+64,0,3,2*p,bar);
 }
      }
    } else if(warp==14){
      const uint32_t tag=epoch();
      if(EARLY) bar_sync(6,288); else bar_sync(3,320);
      if(lane==0){ bulk_s2g(g_kvb+((size_t)(4*hh)*16+m)*8192, cb+SKV, 16384); bulk_commit(); bulk_wait<0>();
        flag_set_rlx(&g_tile[(4*hh)*16+m],tag);
        flag_wait(&g_cnt[C_G+m],8*tag); }
      __syncwarp();
      #pragma unroll
      for(int i=0;i<4;i++) asm volatile("st.shared.f32 [%0], %1;"::"r"(SGATE+(i*32+lane)*4),"f"(__ldcg(g_gate+m*128+i*32+lane)):"memory");
      __syncwarp(); if(lane==0) mbar_arrive(B_W+8);
      for(int r=0;r<4;r++){ bar_sync(2,288);
        if(lane==0){ tma2d_store(&mp.gos,cb+SO,1024+r*256+hh*32,m*128); bulk_commit(); bulk_wait<0>();
          flag_add_rlx(&g_cnt[r<3 ? C_OB+r*16+m : C_OP+4*m+(hh>>1)]); mbar_arrive(B_O); }
        __syncwarp(); }
    } else {
      const uint32_t tag=ld_acq(&g_epoch)+1;
      if(lane==0){ asm volatile("st.shared.u32 [%0], %1;"::"r"(SEP),"r"(tag):"memory"); mbar_arrive(B_E); }
      #pragma unroll
      for(int i=0;i<5;i++) *(float4*)(g_kv+((tag+1)&1)*81920+blockIdx.x*640+i*128+lane*4)=make_float4(0.f,0.f,0.f,0.f);
      if(lane==0) flag_wait_eq(&g_tile[(4*hh+1)*16+m],tag);
      bar_sync(4,160);
      if(lane==0){
        #pragma unroll
        for(int j=0;j<2;j++){ bulk_s2g(g_q+((size_t)(4*hh+2+j)*2048+m*128)*32, cb+SG+3*32768+j*8192, 8192); bulk_s2g(g_kvb+((size_t)(4*hh+2+j)*16+m)*8192, cb+SG+3*32768+16384+j*8192, 8192); }
        bulk_commit(); bulk_wait_read<0>(); }
      __syncwarp();
      if(lane<8) mbar_arrive_cl(mapa(B_GE+24,lane&1));
      if(lane==0){ bulk_wait<0>(); flag_set_rlx(&g_tile[(4*hh+2)*16+m],tag); flag_set_rlx(&g_tile[(4*hh+3)*16+m],tag); }
      bar_sync(4,160);
      if(lane==0){ flag_add(&g_cnt[C_KV+hh]); flag_wait(&g_cnt[C_KV+hh],16*tag); }
      __syncwarp();
      const int f=m*16+(lane>>1), c0=(lane&1)*2; const float* src=g_kv+(tag&1)*81920+((size_t)hh*256+f)*40;
      #pragma unroll
      for(int c=c0;c<c0+2;c++){ const float4 a=__ldcg((const float4*)(src+c*8)), b=__ldcg((const float4*)(src+c*8+4));
        g_kvi[hh*1280+f*4+(c^((f>>1)&3))]=make_uint4(pack(a.x,a.y),pack(a.z,a.w),pack(b.x,b.y),pack(b.z,b.w)); }
      if((lane&1)==0) g_kvi[hh*1280+1024+(f&63)*4+((f>>6)^((f>>1)&3))]=make_uint4(pack(__ldcg(src+32),1.f),0u,0u,0u);
      __syncwarp();
      if(lane==0){ flag_add(&g_cnt[C_KI+hh]); }
      bar_sync(4,160);
      if(lane==0){ tma2d_store(&mp.go,cb+SG+3*32768,hh*128,m*128); tma2d_store(&mp.go,cb+SG+3*32768+16384,hh*128+64,m*128); bulk_commit(); bulk_wait_read<0>(); }
      __syncwarp();
      if(lane<8) mbar_arrive_cl(mapa(B_GE+24,lane&1));
      if(lane==0){ bulk_wait<0>(); flag_add_rlx(&g_cnt[C_OA+m]); }
    }
  } else if(warp>=8){
    const int wq=warp-8, t128=tid-256;
    uint32_t zz; asm volatile("mov.u32 %0, 0;":"=r"(zz)); zz=__shfl_sync(0xffffffffu,zz,0);
    int s=0; uint32_t ph=0;
    const uint32_t rel=mapa(B_GE,lane&1);
    auto release=[&](int slot){ if(lane<2) mbar_arrive_cl(rel+8*slot); };
    const int srow=wq*16+(lane&15);
    {
      #pragma unroll 1
      for(int r=0;r<4;r++){ const int row=m*128+hh*16+wq*4+r; float gs=0;
        #pragma unroll
        for(int j=0;j<4;j++){ const uint4 a=__ldg((const uint4*)(mp.xp+(size_t)row*1024+j*256+lane*8)), b=__ldg((const uint4*)(mp.gw+j*256+lane*8));
          const __nv_bfloat162* pa=(const __nv_bfloat162*)&a; const __nv_bfloat162* pb=(const __nv_bfloat162*)&b;
          #pragma unroll
          for(int e=0;e<4;e++){ float2 p=__bfloat1622float2(__hmul2(pa[e],pb[e])); gs+=p.x+p.y; } }
        #pragma unroll
        for(int o=16;o;o>>=1) gs+=__shfl_xor_sync(0xffffffffu,gs,o);
        gs=__bfloat162float(__float2bfloat16(gs));
        if(lane==0) g_gate[row]=__bfloat162float(__float2bfloat16(1.f/(1.f+__expf(-gs)))); }
      bar_sync(1,128);
      if(t128==0) flag_add(&g_cnt[C_G+m]);
      bar_sync(5,384);
      #pragma unroll
      for(int i=0;i<(THR ? 3 : 4);i++) release(i);
    }
    reg_alloc<RG>();
    #pragma unroll 1
    for(int job=-1;job<4;job++){
      float acc[2][64];
      auto stage=[&](const bool z, const bool rl, const int G, const int W){
        mbar_wait(B_GF+8*s,ph);
        const uint32_t ad=((SG+s*32768)>>4)|(1u<<16), bd=((SG+s*32768+16384)>>4)|((8192u>>4)<<16);
        auto wt=[&]{ wg_commit(); if(W) wg_wait<1>(); else wg_wait<0>(); };
        #pragma unroll
        for(int kk=0;kk<4;kk++){
          if(G==0 || kk%(G?G:1)==0) wg_fence();
          if(z&&kk==0) wgmma_ss_n128z<0,1>(acc[0],mk_desc2(ad,HI128),mk_desc2(bd,HI128));
          else wgmma_ss_n128<0,1>(acc[0],mk_desc2(ad+kk*2,HI128),mk_desc2(bd+kk*128,HI128),1);
          if(G==0){ wt(); if(rl && kk==0) release((s+3)&3); wg_fence(); }
          if(z&&kk==0) wgmma_ss_n128z<0,1>(acc[1],mk_desc2(ad+512,HI128),mk_desc2(bd,HI128));
          else wgmma_ss_n128<0,1>(acc[1],mk_desc2(ad+512+kk*2,HI128),mk_desc2(bd+kk*128,HI128),1);
          if(G==0 || kk%(G?G:1)==G-1){ wt(); if(rl && kk==G-1) release((s+3)&3); }
        }
        s=(s+1)&3; ph^=(s==0); };
      stage(true,false,GCG,GW);
      const int nst = job==3 ? 32 : 16;
      #pragma unroll 1
      for(int st=1;st<nst;st++) stage(false,st<29,GCG,GW);
      wg_wait<0>();
      bar_sync(1,128);
      const uint32_t SCR = SG + (job<2 ? 3*32768 : 0);
      fence_regs(acc[0]); fence_regs(acc[1]);
      if(job<0){
        #pragma unroll
        for(int mb=0;mb<2;mb++){ const int row=mb*64+srow;
          #pragma unroll
          for(int c=0;c<8;c++){ const float* v=&acc[mb][8*c];
            stsm4(cb+SCR+(c>>1)*8192+row*64+((((c&1)*2+(lane>>4))^((row>>1)&3))<<4), pack(v[0],v[1]),pack(v[2],v[3]),pack(v[4],v[5]),pack(v[6],v[7])); } }
        fence_async_smem(); bar_arrive(4,160);
      } else if(job<2){
        if(job==0) mbar_wait(B_W,0);
        uint32_t kf[2][16];
        #pragma unroll
        for(int mb=0;mb<2;mb++){
          #pragma unroll
          for(int i=0;i<16;i++) kf[mb][i]=pack(acc[mb][2*i],acc[mb][2*i+1]);
          const int row=mb*64+srow;
          #pragma unroll
          for(int c=0;c<4;c++){ const float* v=&acc[mb][32+8*c];
            stsm4(cb+SCR+(c>>1)*8192+row*64+((((c&1)*2+(lane>>4))^((row>>1)&3))<<4), pack(v[0],v[1]),pack(v[2],v[3]),pack(v[4],v[5]),pack(v[6],v[7])); }
        }
        float pk[2][2][16];
        wg_fence();
        #pragma unroll
        for(int h=0;h<2;h++){ const uint32_t wd=((SW+(job*2+h)*2048)>>4)|(1u<<16);
          #pragma unroll
          for(int mb=0;mb<2;mb++){
            wgmma_rs_n32z<1>(pk[h][mb],kf[mb][8*h],kf[mb][8*h+1],kf[mb][8*h+2],kf[mb][8*h+3],mk_desc2(wd,HI64));
            wgmma_rs_n32<1>(pk[h][mb],kf[mb][8*h+4],kf[mb][8*h+5],kf[mb][8*h+6],kf[mb][8*h+7],mk_desc2(wd+64,HI64),1); } }
        wg_commit(); wg_wait<0>();
        float kv[20];
        auto put_kv=[&](int h){
          wg_wait<0>(); fence_regs(kv);
          float* dst=g_kv+(epoch()&1)*81920+((size_t)(4*hh+2*job+h)*64+wq*16+(lane>>2))*40+(lane&3)*2;
          #pragma unroll
          for(int j=0;j<4;j++){ red2(dst+8*j,kv[4*j],kv[4*j+1]); red2(dst+320+8*j,kv[4*j+2],kv[4*j+3]); }
          if((lane&3)==0){ red1(dst+32,kv[16]); red1(dst+352,kv[18]); } };
        #pragma unroll
        for(int h=0;h<2;h++){
          fence_regs(pk[h][0]); fence_regs(pk[h][1]);
          uint32_t ph_[2][16];
          #pragma unroll
          for(int mb=0;mb<2;mb++){
            float (&p)[16]=pk[h][mb]; float x0,x1,n0,n1; mnmx(p,x0,x1,n0,n1);
            x0*=-LOG2E; x1*=-LOG2E; n0*=LOG2E; n1*=LOG2E;
            float ep[16],en[16],sp0=0,sp1=0,sn0=0,sn1=0;
            #pragma unroll
            for(int i=0;i<16;i++){ const bool hi=i&2; ep[i]=ex2(fmaf(p[i],LOG2E,hi?x1:x0)); en[i]=ex2(fmaf(p[i],-LOG2E,hi?n1:n0));
              if(hi){ sp1+=ep[i]; sn1+=en[i]; } else { sp0+=ep[i]; sn0+=en[i]; } }
            #pragma unroll
            for(int o=1;o<4;o<<=1){ sp0+=__shfl_xor_sync(0xffffffffu,sp0,o); sp1+=__shfl_xor_sync(0xffffffffu,sp1,o); sn0+=__shfl_xor_sync(0xffffffffu,sn0,o); sn1+=__shfl_xor_sync(0xffffffffu,sn1,o); }
            sp0=rcp(sp0); sp1=rcp(sp1); sn0=rcp(sn0); sn1=rcp(sn1);
            #pragma unroll
            for(int i=0;i<8;i++){ const bool hi=i&1; ph_[mb][i]=pack(ep[2*i]*(hi?sp1:sp0),ep[2*i+1]*(hi?sp1:sp0)); ph_[mb][8+i]=pack(en[2*i]*(hi?sn1:sn0),en[2*i+1]*(hi?sn1:sn0)); }
          }
          if(h==1){
            #pragma unroll
            for(int i=0;i<16;i++) asm volatile(""::"r"(ph_[0][i]),"r"(ph_[1][i]));
            put_kv(0); bar_sync(1,128); }
          #pragma unroll
          for(int mb=0;mb<2;mb++){ const int row=mb*64+srow;
            #pragma unroll
            for(int c=0;c<4;c++) stsm4(cb+SCR+16384+row*128+(((2*c+(lane>>4))^(row&7))<<4), ph_[mb][4*c],ph_[mb][4*c+1],ph_[mb][4*c+2],ph_[mb][4*c+3]); }
          fence_async_smem(); bar_sync(1,128);
          const uint32_t pd=((SCR+16384)>>4)|(1u<<16), vd=((SCR+h*8192)>>4)|(((SONES-SCR-h*8192)>>4)<<16);
          wg_fence();
          wgmma_ss_n40z<1,1>(kv,mk_desc2(pd,HI128),mk_desc2(vd,HI64));
          #pragma unroll
          for(int ks=1;ks<8;ks++) wgmma_ss_n40<1,1>(kv,mk_desc2(pd+ks*128,HI128),mk_desc2(vd+ks*(64u-(64u<<16)),HI64),1);
          wg_commit();
        }
        put_kv(1);
        release(3);
        if(job==1) bar_arrive(4,160);
      } else if(job==2){
        uint32_t qf[2][32];
        #pragma unroll
        for(int mb=0;mb<2;mb++){
          #pragma unroll
          for(int i=0;i<32;i++) qf[mb][i]=pack(acc[mb][2*i],acc[mb][2*i+1]); }
        float pq[2][16], op[20], on[20]; uint32_t e[2][16];
        auto PQ=[&](const int i){ const int h=i>>1, mb=i&1; const uint32_t wd=((SW+h*2048)>>4)|(1u<<16);
          wgmma_rs_n32z<1>(pq[mb],qf[mb][8*h],qf[mb][8*h+1],qf[mb][8*h+2],qf[mb][8*h+3],mk_desc2(wd,HI64));
          wgmma_rs_n32<1>(pq[mb],qf[mb][8*h+4],qf[mb][8*h+5],qf[mb][8*h+6],qf[mb][8*h+7],mk_desc2(wd+64,HI64),1); };
        auto EX=[&](const int b){
          float (&p)[16]=pq[b]; fence_regs(p); float x0,x1,n0,n1; mnmx(p,x0,x1,n0,n1);
          x0*=-LOG2E; x1*=-LOG2E; n0*=LOG2E; n1*=LOG2E;
          #pragma unroll
          for(int i=0;i<8;i++){ const bool hi=i&1;
            e[b][i]=pack(ex2(fmaf(p[2*i],LOG2E,hi?x1:x0)),ex2(fmaf(p[2*i+1],LOG2E,hi?x1:x0)));
            e[b][8+i]=pack(ex2(fmaf(p[2*i],-LOG2E,hi?n1:n0)),ex2(fmaf(p[2*i+1],-LOG2E,hi?n1:n0))); }
          #pragma unroll
          for(int i=0;i<16;i++) asm volatile(""::"r"(e[b][i])); };
        wg_fence(); PQ(0); PQ(1); wg_commit(); wg_wait<0>();
        EX(0);
        mbar_wait(B_GF,ph); mbar_wait(B_W+8,0);
        float gt[4];
        #pragma unroll
        for(int i=0;i<4;i++) asm volatile("ld.shared.f32 %0, [%1];":"=f"(gt[i]):"r"(SGATE+((i>>1)*64+(i&1)*8+wq*16+(lane>>2))*4));
        #pragma unroll
        for(int i=0;i<8;i++){ const int h=i>>1, mb=i&1;
          const uint32_t kd=((SCR+h*4096)>>4)|(((16384+16*h-h*4096)>>4)<<16);
          wg_fence();
          wgmma_rs_n40z<1>(op,e[mb][0],e[mb][1],e[mb][2],e[mb][3],mk_desc2(kd,HI64));
          wgmma_rs_n40<1>(op,e[mb][4],e[mb][5],e[mb][6],e[mb][7],mk_desc2(kd+64,HI64),1);
          wgmma_rs_n40z<1>(on,e[mb][8],e[mb][9],e[mb][10],e[mb][11],mk_desc2(kd+128,HI64));
          wgmma_rs_n40<1>(on,e[mb][12],e[mb][13],e[mb][14],e[mb][15],mk_desc2(kd+192,HI64),1);
          if(i<6) PQ(i+2);
          wg_commit();
          if(i<7) EX(mb^1);
          BOUND(40+i);
          wg_wait<0>(); fence_regs(op); fence_regs(on);
          float a0=rcp(op[17]), b0=rcp(on[17]), a1=rcp(op[19]), b1=rcp(on[19]);
          const float f0=__fdividef(gt[2*mb],op[16]*a0+on[16]*b0+1e-6f), f1=__fdividef(gt[2*mb+1],op[18]*a1+on[18]*b1+1e-6f);
          a0=__shfl_sync(0xffffffffu,a0*f0,lane&28); b0=__shfl_sync(0xffffffffu,b0*f0,lane&28);
          a1=__shfl_sync(0xffffffffu,a1*f1,lane&28); b1=__shfl_sync(0xffffffffu,b1*f1,lane&28);
          const int row=mb*64+srow;
          #pragma unroll
          for(int c=0;c<2;c++){ const float* p=&op[8*c]; const float* n=&on[8*c];
            stsm4(cb+SG+3*32768+(h>>1)*16384+row*128+((((h&1)*4+c*2+(lane>>4))^(row&7))<<4),
                  pack(p[0]*a0+n[0]*b0,p[1]*a0+n[1]*b0),pack(p[2]*a1+n[2]*b1,p[3]*a1+n[3]*b1),pack(p[4]*a0+n[4]*b0,p[5]*a0+n[5]*b0),pack(p[6]*a1+n[6]*b1,p[7]*a1+n[7]*b1)); }
        }
        fence_async_smem();
        release(0); s=1;
        bar_arrive(4,160);
      } else {
        #pragma unroll
        for(int mb=0;mb<2;mb++){ const int row=mb*64+srow;
          #pragma unroll
          for(int c=0;c<8;c++){ const float* v=&acc[mb][8*c];
            stsm4(cb+SCR+(c>>2)*16384+row*128+((((c&3)*2+(lane>>4))^(row&7))<<4), pack(v[0],v[1]),pack(v[2],v[3]),pack(v[4],v[5]),pack(v[6],v[7])); } }
        fence_async_smem(); bar_sync(1,128);
        if(t128==0){ tma2d_store(&mp.out,cb+SCR,hh*128,m*128); tma2d_store(&mp.out,cb+SCR+16384,hh*128+64,m*128); bulk_commit();
          if(blockIdx.x==0) g_epoch=epoch();
          bulk_wait_read<0>(); }
      }
    }
  } else {
    reg_alloc<168>();
    constexpr uint32_t kd0=(SKV>>4)|(1u<<16), vd0=((SKV+8192)>>4)|(((SONES-SKV-8192)>>4)<<16);
    {
      const uint32_t prel=mapa(B_PE,lane&1); const int row=warp*16+(lane&15);
      const uint32_t so=cb+row*64, sx=(row>>1)&3;
      float acc[2][64];
      auto pa=[&](const int k, const bool z){
        const int ps=k&3;
        mbar_wait(B_PF+8*ps,(k>>2)&1);
        const uint32_t ad=((PR+ps*PST+(warp>>2)*8192)>>4)|(1u<<16), bd=((PR+ps*PST+16384)>>4)|((8192u>>4)<<16);
        wg_fence();
        #pragma unroll
        for(int kk=0;kk<4;kk++){
          #pragma unroll
          for(int nb=0;nb<2;nb++){
            if(z&&kk==0) wgmma_ss_n128z<0,1>(acc[nb],mk_desc2(ad,HI128),mk_desc2(bd+nb*1024,HI128));
            else wgmma_ss_n128<0,1>(acc[nb],mk_desc2(ad+kk*2,HI128),mk_desc2(bd+nb*1024+kk*128,HI128),1); }
          if(kk==0){ wg_commit(); wg_wait<1>(); if(!z && k<13 && lane<2) mbar_arrive_cl(prel+8*((k+3)&3)); wg_fence(); } }
        wg_commit(); };
      pa(0,true);
      #pragma unroll 1
      for(int k=1;k<16;k++) pa(k,false);
      wg_wait<0>(); fence_regs(acc[0]); fence_regs(acc[1]);
      bar_sync(5,384);
      auto put=[&](const int c){ const float* v=&acc[c>>3][8*(c&7)]; const int j=(c>>1)&1, bx=c>>2;
        stsm4(so+(bx==0 ? SQ+j*8192 : bx<3 ? SKV+j*49152+(bx-1)*8192 : SW+j*8192)+((((c&1)*2+(lane>>4))^sx)<<4), pack(v[0],v[1]),pack(v[2],v[3]),pack(v[4],v[5]),pack(v[6],v[7])); };
      put(4); put(5); put(8); put(9);
      fence_async_smem(); bar_arrive(6,288);
      put(0); put(1); put(2); put(3); put(6); put(7); put(10); put(11); put(12); put(13); put(14); put(15);
      fence_async_smem(); bar_sync(3,288);
    }
    reg_dealloc<RA>();
    float o[20], S0[32], S1[32], nb0=0, nb1=0; uint32_t P0[16], P1[16];
    #pragma unroll
    for(int i=0;i<20;i++) o[i]=0;
    #pragma unroll
    for(int i=0;i<16;i++) P1[i]=0;
    fence_regs(o);
    uint32_t qf[8];
    auto ldq=[&](int u){ uint32_t t; asm volatile("mov.u32 %0, %%tid.x;":"=r"(t));
      const uint32_t row=(t>>5)*16+(t&15), a=cb+SQ+(u&1)*8192+row*64;
      #pragma unroll
      for(int kk=0;kk<2;kk++) asm volatile("ldmatrix.sync.aligned.m8n8.x4.shared.b16 {%0,%1,%2,%3}, [%4];":"=r"(qf[4*kk]),"=r"(qf[4*kk+1]),"=r"(qf[4*kk+2]),"=r"(qf[4*kk+3])
        :"r"(a+(((2*kk+((t>>4)&1))^((row>>1)&3))<<4)):"memory"); };
    ldq(0);
    auto qk=[&](float (&S)[32], uint32_t kd){
      wgmma_rs_n64z<0>(S,qf[0],qf[1],qf[2],qf[3],mk_desc2(kd,HI64));
      wgmma_rs_n64<0>(S,qf[4],qf[5],qf[6],qf[7],mk_desc2(kd+2,HI64),1); };
    wg_fence(); qk(S0,kd0); wg_commit(); wg_wait<0>(); fence_regs(S0);
    auto epi=[&](int r){
      uint32_t cta,t; asm volatile("mov.u32 %0, %%ctaid.x;":"=r"(cta)); asm volatile("mov.u32 %0, %%tid.x;":"=r"(t));
      const int lr=(t>>5)*16+((t&31)>>2), head=4*(cta>>4)+r;
      if(r==0) mbar_wait(B_W+8,0);
      float g0,g1; asm volatile("ld.shared.f32 %0, [%1];":"=f"(g0):"r"(SGATE+lr*4)); asm volatile("ld.shared.f32 %0, [%1];":"=f"(g1):"r"(SGATE+lr*4+32));
      g0=__bfloat162float(__float2bfloat16(1.f-g0)); g1=__bfloat162float(__float2bfloat16(1.f-g1));
      const float f0=__fdividef(g0,o[16]), f1=__fdividef(g1,o[18]);
      if(r>0) mbar_wait(B_O,(r-1)&1);
      float t0=0,t1=0;
      #pragma unroll
      for(int j=0;j<4;j++){ t0+=fabsf(o[4*j])+fabsf(o[4*j+1]); t1+=fabsf(o[4*j+2])+fabsf(o[4*j+3]); }
      { const uint32_t row=(t>>5)*16+(t&15);
        #pragma unroll
        for(int c=0;c<2;c++){ const float* v=&o[8*c];
          stsm4(cb+SO+row*64+(((c*2+((t>>4)&1))^((row>>1)&3))<<4), pack(v[0]*f0,v[1]*f0),pack(v[2]*f1,v[3]*f1),pack(v[4]*f0,v[5]*f0),pack(v[6]*f1,v[7]*f1)); } }
      const unsigned b0=__ballot_sync(0xffffffffu,!(o[16]<1e30f && t0<3e38f)), b1=__ballot_sync(0xffffffffu,!(o[18]<1e30f && t1<3e38f));
      if(b0|b1){
        const int ln=t&31; const uint8_t* kv=(const uint8_t*)(g_kvb+(size_t)head*16*8192);
        #pragma unroll 1
        for(int rr=0;rr<16;rr++){
          if(!(((rr<8?b0:b1)>>((rr&7)*4))&15)) continue;
          const int qrow=(t>>5)*16+rr; const uint32_t qa=cb+SQ+(r&1)*8192+qrow*64;
          auto dot=[&](int key){ float s=0; const uint8_t* kr=kv+(key>>7)*16384+(key&127)*64;
            #pragma unroll 1
            for(int c=0;c<4;c++){ uint4 a=__ldcg((const uint4*)(kr+((c^((key>>1)&3))<<4))), b;
              asm volatile("ld.shared.v4.u32 {%0,%1,%2,%3}, [%4];":"=r"(b.x),"=r"(b.y),"=r"(b.z),"=r"(b.w):"r"(qa+((c^((qrow>>1)&3))<<4)));
              const uint32_t* pa=&a.x; const uint32_t* pb=&b.x;
              #pragma unroll
              for(int e=0;e<4;e++){ s=fmaf(__uint_as_float(pa[e]<<16),__uint_as_float(pb[e]<<16),s); s=fmaf(__uint_as_float(pa[e]&0xffff0000u),__uint_as_float(pb[e]&0xffff0000u),s); } }
            return s; };
          float mx=-INFINITY;
          #pragma unroll 1
          for(int k=ln;k<2048;k+=32) mx=fmaxf(mx,dot(k));
          #pragma unroll
          for(int of=16;of;of>>=1) mx=fmaxf(mx,__shfl_xor_sync(0xffffffffu,mx,of));
          float a=0,l=0;
          #pragma unroll 1
          for(int k0=0;k0<2048;k0+=32){ const float p=ex2((dot(k0+ln)-mx)*SC); l+=p;
            #pragma unroll 1
            for(int j=0;j<32;j++){ const int key=k0+j; const unsigned short vv=__ldcg((const unsigned short*)(kv+(key>>7)*16384+8192+(key&127)*64+(((ln>>3)^((key>>1)&3))<<4)+(ln&7)*2));
              a=fmaf(__shfl_sync(0xffffffffu,p,j),__uint_as_float((uint32_t)vv<<16),a); } }
          #pragma unroll
          for(int of=16;of;of>>=1) l+=__shfl_xor_sync(0xffffffffu,l,of);
          float g; asm volatile("ld.shared.f32 %0, [%1];":"=f"(g):"r"(SGATE+qrow*4));
          g=__bfloat162float(__float2bfloat16(1.f-g));
          __syncwarp();
          asm volatile("st.shared.u16 [%0], %1;"::"r"(cb+SO+qrow*64+(((ln>>3)^((qrow>>1)&3))<<4)+(ln&7)*2),"h"(__bfloat16_as_ushort(__float2bfloat16(a*g/l))):"memory");
        }
      }
      fence_async_smem(); bar_arrive(2,288);
    };
    const bool l0 = lane==0;
    uint32_t zz; asm volatile("mov.u32 %0, 0;":"=r"(zz)); zz=__shfl_sync(0xffffffffu,zz,0);
    uint32_t sp=NST-1, sc=0, sn=1, phn=0;
    auto newmax=[&](float (&S)[32]){
      float m0=S[0],m1=S[2];
      #pragma unroll
      for(int i=0;i<8;i++){ m0=fmaxf(m0,fmaxf(S[4*i],S[4*i+1])); m1=fmaxf(m1,fmaxf(S[4*i+2],S[4*i+3])); }
      m0=fmaxf(m0,__shfl_xor_sync(0xffffffffu,m0,1)); m0=fmaxf(m0,__shfl_xor_sync(0xffffffffu,m0,2));
      m1=fmaxf(m1,__shfl_xor_sync(0xffffffffu,m1,1)); m1=fmaxf(m1,__shfl_xor_sync(0xffffffffu,m1,2));
      nb0=-(m0*SC+OFFS); nb1=-(m1*SC+OFFS); };
    newmax(S0);
    #pragma unroll
    for(int i=0;i<NF;i++) S0[i]=fmaf(S0[i],SC,((i>>1)&1)?nb1:nb0);
    auto step=[&](const int r, const int MODE, const int U, float (&S)[32], uint32_t (&P)[16], float (&Sn)[32], uint32_t (&Pp)[16]){
      const bool first=(U==0)&&MODE==1, second=(U==1)&&MODE==1, last=(U==1)&&MODE==2;
      if(second && r>0) epi(r-1);
      if(last){ if(r==1 || r==2) mbar_wait(B_Q+8*((r+1)&1),0); ldq(r+1); }
      const uint32_t vd= U==0 ? vd0+sp*(1024u-(1024u<<16))+4*(64u-(64u<<16)) : vd0+sc*(1024u-(1024u<<16));
      const uint32_t kd= U==0 ? kd0+sc*1024u+256u : kd0+sn*1024u;
      bool ok=true;
      const float c0=nb0, c1=nb1;
      auto ex=[&](const int i){ if(2*i>=NF) P[i]=pack(ex2(fmaf(S[2*i],SC,(i&1)?c1:c0)),ex2(fmaf(S[2*i+1],SC,(i&1)?c1:c0))); else P[i]=pack(ex2(S[2*i]),ex2(S[2*i+1])); };
      if(U==0 && !(MODE==2 && r==3)) ok=mbar_try(B_KF+8*sn, phn);
      wg_fence();
      qk(Sn,kd); wg_commit();
      #pragma unroll
      for(int kk=0;kk<4;kk++){
        if(second&&kk==0) wgmma_rs_n40z<1>(o,Pp[4*kk],Pp[4*kk+1],Pp[4*kk+2],Pp[4*kk+3],mk_desc2(vd+kk*(64u-(64u<<16)),HI64));
        else wgmma_rs_n40<1>(o,Pp[4*kk],Pp[4*kk+1],Pp[4*kk+2],Pp[4*kk+3],mk_desc2(vd+kk*(64u-(64u<<16)),HI64),1); }
      wg_commit();
      #pragma unroll
      for(int i=0;i<PA;i++) ex(i);
      #pragma unroll
      for(int i=0;i<PA;i++) asm volatile(""::"r"(P[i]));
      if(U==0){ if(__builtin_expect(!ok,0)) mbar_wait(B_KF+8*sn, phn); } else BOUND(1+MODE*8);
      #pragma unroll
      for(int i=PA;i<PART;i++) ex(i);
      #pragma unroll
      for(int i=PA;i<PART;i++) asm volatile(""::"r"(P[i]));
      BOUND(2+U+MODE*8);
      wg_wait<1>(); fence_regs(Sn);
      if(last) newmax(Sn);
      #pragma unroll
      for(int j=0;j<32;j++){
        if((j+1)*NF/32 != j*NF/32){ const int q=j*NF/32; Sn[q]=fmaf(Sn[q],SC,((q>>1)&1)?nb1:nb0); }
        if((j+1)*(16-PART)/32 != j*(16-PART)/32) ex(PART+j*(16-PART)/32); }
      fence_regs(Sn);
      #pragma unroll
      for(int i=PART;i<16;i++) asm volatile(""::"r"(P[i]));
      wg_wait<0>(); fence_regs(o);
      if(U==0){ if(l0 && !(first && r==0)) mbar_arrive(B_KE+8*sp);
      }
      else { sp=sc; sc=sn; sn=sn+1==NST?0:sn+1; phn^=(sn==0); }
    };
    #pragma unroll 1
    for(int r=0;r<4;r++){
      step(r,1,0,S0,P0,S1,P1); step(r,1,1,S1,P1,S0,P0);
      #pragma unroll 1
      for(int t=0;t<14;t++){ step(r,0,0,S0,P0,S1,P1); step(r,0,1,S1,P1,S0,P0); }
      step(r,2,0,S0,P0,S1,P1); step(r,2,1,S1,P1,S0,P0);
    }
    { const uint32_t vd=vd0+sp*(1024u-(1024u<<16))+4*(64u-(64u<<16));
      wg_fence();
      #pragma unroll
      for(int kk=0;kk<4;kk++) wgmma_rs_n40<1>(o,P1[4*kk],P1[4*kk+1],P1[4*kk+2],P1[4*kk+3],mk_desc2(vd+kk*(64u-(64u<<16)),HI64),1);
      wg_commit(); }
    wg_wait<0>(); fence_regs(o);
    epi(3);
  }
}

typedef CUresult (*PFN_enc)(CUtensorMap*, CUtensorMapDataType, cuuint32_t, void*, const cuuint64_t*, const cuuint64_t*, const cuuint32_t*, const cuuint32_t*, CUtensorMapInterleave, CUtensorMapSwizzle, CUtensorMapL2promotion, CUtensorMapFloatOOBfill);
static CUtensorMap mk_map(PFN_enc fn, const void* p, int rank, const cuuint64_t* dims, const cuuint64_t* strides, const cuuint32_t* box, CUtensorMapSwizzle sw){
  CUtensorMap m; cuuint32_t es[4]={1,1,1,1};
  fn(&m, CU_TENSOR_MAP_DATA_TYPE_BFLOAT16, rank, (void*)p, dims, strides, box, es, CU_TENSOR_MAP_INTERLEAVE_NONE, sw, CU_TENSOR_MAP_L2_PROMOTION_L2_256B, CU_TENSOR_MAP_FLOAT_OOB_FILL_NONE);
  return m; }
static CUtensorMap map2d(PFN_enc fn, const void* p, uint64_t inner, uint64_t outer, uint32_t bi, uint32_t bo, CUtensorMapSwizzle sw){
  cuuint64_t d[2]={inner,outer}, s[1]={inner*2}; cuuint32_t b[2]={bi,bo}; return mk_map(fn,p,2,d,s,b,sw); }

extern "C" void kernel_launch(void* const* d_in, const int* in_sizes, int n_in, void* d_out, int out_size){
  static bool init=false; static Maps mp; static const void* key[8];
  const void* cur[8]={d_in[0],d_in[1],d_in[2],d_in[3],d_in[5],d_in[6],d_in[7],d_out};
  bool same=init; for(int i=0;i<8;i++) same = same && key[i]==cur[i];
  if(!same){
    PFN_enc fn=nullptr; cudaDriverEntryPointQueryResult q; cudaGetDriverEntryPoint("cuTensorMapEncodeTiled",(void**)&fn,cudaEnableDefault,&q);
    void* go; cudaGetSymbolAddress(&go,g_o);
    const CUtensorMapSwizzle S128=CU_TENSOR_MAP_SWIZZLE_128B;
    mp.x=map2d(fn,d_in[0],1024,2048,64,128,S128);
    mp.wa=map2d(fn,d_in[1],3072,1024,64,64,S128);
    mp.wb=map2d(fn,d_in[5],3072,1024,64,64,S128);
    mp.go=map2d(fn,go,2048,2048,64,128,S128);
    mp.gos=map2d(fn,go,2048,2048,32,128,CU_TENSOR_MAP_SWIZZLE_64B);
    mp.woa=map2d(fn,d_in[3],1024,1024,64,64,S128);
    { cuuint64_t d[4]={1024,32,4,8}, s[3]={2048,65536,262144}; cuuint32_t b[4]={64,32,1,2}; mp.wob=mk_map(fn,d_in[6],4,d,s,b,S128); }
    mp.out=map2d(fn,d_out,1024,2048,64,128,S128);
    mp.wphi=map2d(fn,d_in[2],32,1024,32,128,CU_TENSOR_MAP_SWIZZLE_64B);
    mp.xp=(const bf16*)d_in[0]; mp.gw=(const bf16*)d_in[7];
    cudaFuncSetAttribute(k_main,cudaFuncAttributeMaxDynamicSharedMemorySize,k2::SMEM);
    for(int i=0;i<8;i++) key[i]=cur[i];
    init=true;
  }
  cudaLaunchConfig_t cfg={}; cfg.gridDim=128; cfg.blockDim=512; cfg.dynamicSmemBytes=k2::SMEM; cfg.stream=cudaStreamPerThread;
  cudaLaunchAttribute at[1];
  at[0].id=cudaLaunchAttributeClusterDimension; at[0].val.clusterDim.x=2; at[0].val.clusterDim.y=1; at[0].val.clusterDim.z=1;
  cfg.attrs=at; cfg.numAttrs=1;
  cudaLaunchKernelEx(&cfg,k_main,mp);
}
```

```cpp
#include <cuda_runtime.h>
#include <cuda_bf16.h>
#include <cuda.h>
#include <stdint.h>

typedef __nv_bfloat16 bf16;
#define DEVI __device__ __forceinline__

DEVI uint32_t smem_u32(const void* p){ return (uint32_t)__cvta_generic_to_shared(p); }
DEVI void mbar_init(uint32_t bar, uint32_t cnt){ asm volatile("mbarrier.init.shared::cta.b64 [%0], %1;"::"r"(bar),"r"(cnt):"memory"); }
DEVI void mbar_expect_tx(uint32_t bar, uint32_t bytes){ asm volatile("mbarrier.arrive.expect_tx.shared::cta.b64 _, [%0], %1;"::"r"(bar),"r"(bytes):"memory"); }
DEVI void mbar_arrive(uint32_t bar){ asm volatile("mbarrier.arrive.shared::cta.b64 _, [%0];"::"r"(bar):"memory"); }
DEVI bool mbar_try(uint32_t bar, uint32_t parity){ uint32_t ok;
  asm volatile("{\n.reg .pred p;\nmbarrier.try_wait.parity.shared::cta.b64 p, [%1], %2;\nselp.u32 %0, 1, 0, p;\n}\n":"=r"(ok):"r"(bar),"r"(parity):"memory"); return ok; }
DEVI void mbar_wait(uint32_t bar, uint32_t parity){
  asm volatile("{\n.reg .pred p;\n.reg .u32 c;\nmov.u32 c, 0;\nLAB_WAIT:\nmbarrier.try_wait.parity.shared::cta.b64 p, [%0], %1;\n@p bra DONE;\nadd.u32 c, c, 1;\nsetp.lt.u32 p, c, 0x200000;\n@p bra LAB_WAIT;\ntrap;\nDONE:\n}\n"::"r"(bar),"r"(parity):"memory"); }
DEVI void tma2d(uint32_t dst, const CUtensorMap* m, int c0, int c1, uint32_t bar){
  asm volatile("cp.async.bulk.tensor.2d.shared::cluster.global.mbarrier::complete_tx::bytes [%0], [%1, {%3, %4}], [%2];"::"r"(dst),"l"(m),"r"(bar),"r"(c0),"r"(c1):"memory"); }
DEVI void tma2d_mc(uint32_t dst, const CUtensorMap* m, int c0, int c1, uint32_t bar, uint16_t mask){
  asm volatile("cp.async.bulk.tensor.2d.shared::cluster.global.mbarrier::complete_tx::bytes.multicast::cluster [%0], [%1, {%3, %4}], [%2], %5;"::"r"(dst),"l"(m),"r"(bar),"r"(c0),"r"(c1),"h"(mask):"memory"); }
DEVI void tma3d_mc(uint32_t dst, const CUtensorMap* m, int c0, int c1, int c2, uint32_t bar, uint16_t mask){
  asm volatile("cp.async.bulk.tensor.3d.shared::cluster.global.mbarrier::complete_tx::bytes.multicast::cluster [%0], [%1, {%3, %4, %5}], [%2], %6;"::"r"(dst),"l"(m),"r"(bar),"r"(c0),"r"(c1),"r"(c2),"h"(mask):"memory"); }
DEVI void tma4d_mc(uint32_t dst, const CUtensorMap* m, int c0, int c1, int c2, int c3, uint32_t bar, uint16_t mask){
  asm volatile("cp.async.bulk.tensor.4d.shared::cluster.global.mbarrier::complete_tx::bytes.multicast::cluster [%0], [%1, {%3, %4, %5, %6}], [%2], %7;"::"r"(dst),"l"(m),"r"(bar),"r"(c0),"r"(c1),"r"(c2),"r"(c3),"h"(mask):"memory"); }
DEVI void tma4d(uint32_t dst, const CUtensorMap* m, int c0, int c1, int c2, int c3, uint32_t bar){
  asm volatile("cp.async.bulk.tensor.4d.shared::cluster.global.mbarrier::complete_tx::bytes [%0], [%1, {%3, %4, %5, %6}], [%2];"::"r"(dst),"l"(m),"r"(bar),"r"(c0),"r"(c1),"r"(c2),"r"(c3):"memory"); }
DEVI uint32_t mapa(uint32_t a, uint32_t rank){ uint32_t r; asm("mapa.shared::cluster.u32 %0, %1, %2;":"=r"(r):"r"(a),"r"(rank)); return r; }
DEVI void mbar_arrive_cl(uint32_t a){ asm volatile("mbarrier.arrive.shared::cluster.b64 _, [%0];"::"r"(a):"memory"); }
DEVI void cluster_sync(){ asm volatile("barrier.cluster.arrive.relaxed.aligned;\nbarrier.cluster.wait.acquire.aligned;":::"memory"); }
DEVI void tma3d(uint32_t dst, const CUtensorMap* m, int c0, int c1, int c2, uint32_t bar){
  asm volatile("cp.async.bulk.tensor.3d.shared::cluster.global.mbarrier::complete_tx::bytes [%0], [%1, {%3, %4, %5}], [%2];"::"r"(dst),"l"(m),"r"(bar),"r"(c0),"r"(c1),"r"(c2):"memory"); }
DEVI void tma2d_store(const CUtensorMap* m, uint32_t src, int c0, int c1){
  asm volatile("cp.async.bulk.tensor.2d.global.shared::cta.bulk_group [%0, {%2, %3}], [%1];"::"l"(m),"r"(src),"r"(c0),"r"(c1):"memory"); }
DEVI void bulk_g2s(uint32_t dst, const void* src, uint32_t bytes, uint32_t bar){
  asm volatile("cp.async.bulk.shared::cluster.global.mbarrier::complete_tx::bytes [%0], [%1], %2, [%3];"::"r"(dst),"l"(src),"r"(bytes),"r"(bar):"memory"); }
DEVI void bulk_s2g(void* dst, uint32_t src, uint32_t bytes){
  asm volatile("cp.async.bulk.global.shared::cta.bulk_group [%0], [%1], %2;"::"l"(dst),"r"(src),"r"(bytes):"memory"); }
DEVI void bulk_commit(){ asm volatile("cp.async.bulk.commit_group;":::"memory"); }
template<int N> DEVI void bulk_wait(){ asm volatile("cp.async.bulk.wait_group %0;"::"n"(N):"memory"); }
template<int N> DEVI void bulk_wait_read(){ asm volatile("cp.async.bulk.wait_group.read %0;"::"n"(N):"memory"); }
DEVI void fence_async_smem(){ asm volatile("fence.proxy.async.shared::cta;":::"memory"); }
DEVI void fence_async_all(){ asm volatile("fence.proxy.async.global;":::"memory"); }
DEVI void wg_fence(){ asm volatile("wgmma.fence.sync.aligned;":::"memory"); }
DEVI void wg_commit(){ asm volatile("wgmma.commit_group.sync.aligned;":::"memory"); }
template<int N> DEVI void wg_wait(){ asm volatile("wgmma.wait_group.sync.aligned %0;"::"n"(N):"memory"); }
DEVI uint64_t mk_desc2(uint32_t lo, uint32_t hi){ uint64_t d; asm("mov.b64 %0, {%1,%2};":"=l"(d):"r"(lo),"r"(hi)); return d; }
template<int R> DEVI void reg_alloc(){ asm volatile("setmaxnreg.inc.sync.aligned.u32 %0;"::"n"(R)); }
template<int R> DEVI void reg_dealloc(){ asm volatile("setmaxnreg.dec.sync.aligned.u32 %0;"::"n"(R)); }
template<int N> DEVI void fence_regs(float (&r)[N]){
  #pragma unroll
  for(int i=0;i<N;i++) asm volatile("":"+f"(r[i])::"memory"); }
DEVI void griddep_wait(){ asm volatile("griddepcontrol.wait;":::"memory"); }
DEVI void bar_sync(int id, int n){ asm volatile("bar.sync %0, %1;"::"r"(id),"r"(n):"memory"); }
DEVI void bar_arrive(int id, int n){ asm volatile("bar.arrive %0, %1;"::"r"(id),"r"(n):"memory"); }
DEVI float ex2(float x){ float y; asm("ex2.approx.ftz.f32 %0,%1;":"=f"(y):"f"(x)); return y; }
DEVI float rcp(float x){ float y; asm("rcp.approx.ftz.f32 %0,%1;":"=f"(y):"f"(x)); return y; }
DEVI uint32_t pack(float lo,float hi){ uint32_t y; asm("cvt.rn.bf16x2.f32 %0,%1,%2;":"=r"(y):"f"(hi),"f"(lo)); return y; }
DEVI void stsm4(uint32_t a, uint32_t r0, uint32_t r1, uint32_t r2, uint32_t r3){
  asm volatile("stmatrix.sync.aligned.m8n8.x4.shared.b16 [%0], {%1,%2,%3,%4};"::"r"(a),"r"(r0),"r"(r1),"r"(r2),"r"(r3):"memory"); }
DEVI void flag_add(unsigned* p){ asm volatile("fence.acq_rel.gpu;\nred.relaxed.gpu.global.add.u32 [%0], 1;"::"l"(p):"memory"); }
DEVI unsigned ld_acq(const unsigned* p){ unsigned v; asm volatile("ld.acquire.gpu.global.u32 %0, [%1];":"=r"(v):"l"(p):"memory"); return v; }
DEVI void flag_set(unsigned* p, unsigned v){ asm volatile("st.release.gpu.global.u32 [%0], %1;"::"l"(p),"r"(v):"memory"); }
DEVI void flag_set_rlx(unsigned* p, unsigned v){ asm volatile("fence.proxy.async.global;\nst.relaxed.gpu.global.u32 [%0], %1;"::"l"(p),"r"(v):"memory"); }
DEVI void flag_add_rlx(unsigned* p){ asm volatile("fence.proxy.async.global;\nred.relaxed.gpu.global.add.u32 [%0], 1;"::"l"(p):"memory"); }
DEVI void flag_wait(const unsigned* p, unsigned target){
  for(int i=0;i<(1<<22);i++){ if((int)(ld_acq(p)-target)>=0) return; __nanosleep(40); }
  asm volatile("trap;"); }
DEVI void flag_wait_eq(const unsigned* p, unsigned tag){
  for(int i=0;i<(1<<22);i++){ if(ld_acq(p)==tag) return; __nanosleep(40); }
  asm volatile("trap;"); }
DEVI void red2(float* p, float a, float b){ asm volatile("red.relaxed.gpu.global.add.v2.f32 [%0], {%1,%2};"::"l"(p),"f"(a),"f"(b):"memory"); }
DEVI void red1(float* p, float a){ asm volatile("red.relaxed.gpu.global.add.f32 [%0], %1;"::"l"(p),"f"(a):"memory"); }
#define BOUND(c) asm volatile("{\n.reg .pred p;\nsetp.eq.u32 p, %0, %1;\n@p exit;\n}\n"::"r"(zz),"r"(c):"memory")
template<int TA, int TB> DEVI void wgmma_ss_n128(float (&d)[64], uint64_t da, uint64_t db, int sd){
  asm volatile("{\n.reg .pred p;\nsetp.ne.b32 p, %66, 0;\n"
    "wgmma.mma_async.sync.aligned.m64n128k16.f32.bf16.bf16 {%0, %1, %2, %3, %4, %5, %6, %7, %8, %9, %10, %11, %12, %13, %14, %15, %16, %17, %18, %19, %20, %21, %22, %23, %24, %25, %26, %27, %28, %29, %30, %31, %32, %33, %34, %35, %36, %37, %38, %39, %40, %41, %42, %43, %44, %45, %46, %47, %48, %49, %50, %51, %52, %53, %54, %55, %56, %57, %58, %59, %60, %61, %62, %63}, %64, %65, p, 1, 1, %67, %68;\n}\n"
    : "+f"(d[0]), "+f"(d[1]), "+f"(d[2]), "+f"(d[3]), "+f"(d[4]), "+f"(d[5]), "+f"(d[6]), "+f"(d[7]), "+f"(d[8]), "+f"(d[9]), "+f"(d[10]), "+f"(d[11]), "+f"(d[12]), "+f"(d[13]), "+f"(d[14]), "+f"(d[15]), "+f"(d[16]), "+f"(d[17]), "+f"(d[18]), "+f"(d[19]), "+f"(d[20]), "+f"(d[21]), "+f"(d[22]), "+f"(d[23]), "+f"(d[24]), "+f"(d[25]), "+f"(d[26]), "+f"(d[27]), "+f"(d[28]), "+f"(d[29]), "+f"(d[30]), "+f"(d[31]), "+f"(d[32]), "+f"(d[33]), "+f"(d[34]), "+f"(d[35]), "+f"(d[36]), "+f"(d[37]), "+f"(d[38]), "+f"(d[39]), "+f"(d[40]), "+f"(d[41]), "+f"(d[42]), "+f"(d[43]), "+f"(d[44]), "+f"(d[45]), "+f"(d[46]), "+f"(d[47]), "+f"(d[48]), "+f"(d[49]), "+f"(d[50]), "+f"(d[51]), "+f"(d[52]), "+f"(d[53]), "+f"(d[54]), "+f"(d[55]), "+f"(d[56]), "+f"(d[57]), "+f"(d[58]), "+f"(d[59]), "+f"(d[60]), "+f"(d[61]), "+f"(d[62]), "+f"(d[63])
    : "l"(da), "l"(db), "r"(sd), "n"(TA), "n"(TB));
}
template<int TA, int TB> DEVI void wgmma_ss_n128z(float (&d)[64], uint64_t da, uint64_t db){
  asm volatile("{\n.reg .pred p;\nsetp.ne.b32 p, 0, 0;\n"
    "wgmma.mma_async.sync.aligned.m64n128k16.f32.bf16.bf16 {%0, %1, %2, %3, %4, %5, %6, %7, %8, %9, %10, %11, %12, %13, %14, %15, %16, %17, %18, %19, %20, %21, %22, %23, %24, %25, %26, %27, %28, %29, %30, %31, %32, %33, %34, %35, %36, %37, %38, %39, %40, %41, %42, %43, %44, %45, %46, %47, %48, %49, %50, %51, %52, %53, %54, %55, %56, %57, %58, %59, %60, %61, %62, %63}, %64, %65, p, 1, 1, %66, %67;\n}\n"
    : "=f"(d[0]), "=f"(d[1]), "=f"(d[2]), "=f"(d[3]), "=f"(d[4]), "=f"(d[5]), "=f"(d[6]), "=f"(d[7]), "=f"(d[8]), "=f"(d[9]), "=f"(d[10]), "=f"(d[11]), "=f"(d[12]), "=f"(d[13]), "=f"(d[14]), "=f"(d[15]), "=f"(d[16]), "=f"(d[17]), "=f"(d[18]), "=f"(d[19]), "=f"(d[20]), "=f"(d[21]), "=f"(d[22]), "=f"(d[23]), "=f"(d[24]), "=f"(d[25]), "=f"(d[26]), "=f"(d[27]), "=f"(d[28]), "=f"(d[29]), "=f"(d[30]), "=f"(d[31]), "=f"(d[32]), "=f"(d[33]), "=f"(d[34]), "=f"(d[35]), "=f"(d[36]), "=f"(d[37]), "=f"(d[38]), "=f"(d[39]), "=f"(d[40]), "=f"(d[41]), "=f"(d[42]), "=f"(d[43]), "=f"(d[44]), "=f"(d[45]), "=f"(d[46]), "=f"(d[47]), "=f"(d[48]), "=f"(d[49]), "=f"(d[50]), "=f"(d[51]), "=f"(d[52]), "=f"(d[53]), "=f"(d[54]), "=f"(d[55]), "=f"(d[56]), "=f"(d[57]), "=f"(d[58]), "=f"(d[59]), "=f"(d[60]), "=f"(d[61]), "=f"(d[62]), "=f"(d[63])
    : "l"(da), "l"(db), "n"(TA), "n"(TB));
}
template<int TB> DEVI void wgmma_rs_n40(float (&d)[20], uint32_t a0, uint32_t a1, uint32_t a2, uint32_t a3, uint64_t db, int sd){
  asm volatile("{\n.reg .pred p;\nsetp.ne.b32 p, %25, 0;\n"
    "wgmma.mma_async.sync.aligned.m64n40k16.f32.bf16.bf16 {%0, %1, %2, %3, %4, %5, %6, %7, %8, %9, %10, %11, %12, %13, %14, %15, %16, %17, %18, %19}, {%20,%21,%22,%23}, %24, p, 1, 1, %26;\n}\n"
    : "+f"(d[0]), "+f"(d[1]), "+f"(d[2]), "+f"(d[3]), "+f"(d[4]), "+f"(d[5]), "+f"(d[6]), "+f"(d[7]), "+f"(d[8]), "+f"(d[9]), "+f"(d[10]), "+f"(d[11]), "+f"(d[12]), "+f"(d[13]), "+f"(d[14]), "+f"(d[15]), "+f"(d[16]), "+f"(d[17]), "+f"(d[18]), "+f"(d[19])
    : "r"(a0), "r"(a1), "r"(a2), "r"(a3), "l"(db), "r"(sd), "n"(TB));
}
template<int TB> DEVI void wgmma_rs_n40z(float (&d)[20], uint32_t a0, uint32_t a1, uint32_t a2, uint32_t a3, uint64_t db){
  asm volatile("{\n.reg .pred p;\nsetp.ne.b32 p, 0, 0;\n"
    "wgmma.mma_async.sync.aligned.m64n40k16.f32.bf16.bf16 {%0, %1, %2, %3, %4, %5, %6, %7, %8, %9, %10, %11, %12, %13, %14, %15, %16, %17, %18, %19}, {%20,%21,%22,%23}, %24, p, 1, 1, %25;\n}\n"
    : "=f"(d[0]), "=f"(d[1]), "=f"(d[2]), "=f"(d[3]), "=f"(d[4]), "=f"(d[5]), "=f"(d[6]), "=f"(d[7]), "=f"(d[8]), "=f"(d[9]), "=f"(d[10]), "=f"(d[11]), "=f"(d[12]), "=f"(d[13]), "=f"(d[14]), "=f"(d[15]), "=f"(d[16]), "=f"(d[17]), "=f"(d[18]), "=f"(d[19])
    : "r"(a0), "r"(a1), "r"(a2), "r"(a3), "l"(db), "n"(TB));
}
template<int TA, int TB> DEVI void wgmma_ss_n40(float (&d)[20], uint64_t da, uint64_t db, int sd){
  asm volatile("{\n.reg .pred p;\nsetp.ne.b32 p, %22, 0;\n"
    "wgmma.mma_async.sync.aligned.m64n40k16.f32.bf16.bf16 {%0, %1, %2, %3, %4, %5, %6, %7, %8, %9, %10, %11, %12, %13, %14, %15, %16, %17, %18, %19}, %20, %21, p, 1, 1, %23, %24;\n}\n"
    : "+f"(d[0]), "+f"(d[1]), "+f"(d[2]), "+f"(d[3]), "+f"(d[4]), "+f"(d[5]), "+f"(d[6]), "+f"(d[7]), "+f"(d[8]), "+f"(d[9]), "+f"(d[10]), "+f"(d[11]), "+f"(d[12]), "+f"(d[13]), "+f"(d[14]), "+f"(d[15]), "+f"(d[16]), "+f"(d[17]), "+f"(d[18]), "+f"(d[19])
    : "l"(da), "l"(db), "r"(sd), "n"(TA), "n"(TB));
}
template<int TA, int TB> DEVI void wgmma_ss_n40z(float (&d)[20], uint64_t da, uint64_t db){
  asm volatile("{\n.reg .pred p;\nsetp.ne.b32 p, 0, 0;\n"
    "wgmma.mma_async.sync.aligned.m64n40k16.f32.bf16.bf16 {%0, %1, %2, %3, %4, %5, %6, %7, %8, %9, %10, %11, %12, %13, %14, %15, %16, %17, %18, %19}, %20, %21, p, 1, 1, %22, %23;\n}\n"
    : "=f"(d[0]), "=f"(d[1]), "=f"(d[2]), "=f"(d[3]), "=f"(d[4]), "=f"(d[5]), "=f"(d[6]), "=f"(d[7]), "=f"(d[8]), "=f"(d[9]), "=f"(d[10]), "=f"(d[11]), "=f"(d[12]), "=f"(d[13]), "=f"(d[14]), "=f"(d[15]), "=f"(d[16]), "=f"(d[17]), "=f"(d[18]), "=f"(d[19])
    : "l"(da), "l"(db), "n"(TA), "n"(TB));
}
template<int TB> DEVI void wgmma_rs_n32(float (&d)[16], uint32_t a0, uint32_t a1, uint32_t a2, uint32_t a3, uint64_t db, int sd){
  asm volatile("{\n.reg .pred p;\nsetp.ne.b32 p, %21, 0;\n"
    "wgmma.mma_async.sync.aligned.m64n32k16.f32.bf16.bf16 {%0, %1, %2, %3, %4, %5, %6, %7, %8, %9, %10, %11, %12, %13, %14, %15}, {%16,%17,%18,%19}, %20, p, 1, 1, %22;\n}\n"
    : "+f"(d[0]), "+f"(d[1]), "+f"(d[2]), "+f"(d[3]), "+f"(d[4]), "+f"(d[5]), "+f"(d[6]), "+f"(d[7]), "+f"(d[8]), "+f"(d[9]), "+f"(d[10]), "+f"(d[11]), "+f"(d[12]), "+f"(d[13]), "+f"(d[14]), "+f"(d[15])
    : "r"(a0), "r"(a1), "r"(a2), "r"(a3), "l"(db), "r"(sd), "n"(TB));
}
template<int TB> DEVI void wgmma_rs_n32z(float (&d)[16], uint32_t a0, uint32_t a1, uint32_t a2, uint32_t a3, uint64_t db){
  asm volatile("{\n.reg .pred p;\nsetp.ne.b32 p, 0, 0;\n"
    "wgmma.mma_async.sync.aligned.m64n32k16.f32.bf16.bf16 {%0, %1, %2, %3, %4, %5, %6, %7, %8, %9, %10, %11, %12, %13, %14, %15}, {%16,%17,%18,%19}, %20, p, 1, 1, %21;\n}\n"
    : "=f"(d[0]), "=f"(d[1]), "=f"(d[2]), "=f"(d[3]), "=f"(d[4]), "=f"(d[5]), "=f"(d[6]), "=f"(d[7]), "=f"(d[8]), "=f"(d[9]), "=f"(d[10]), "=f"(d[11]), "=f"(d[12]), "=f"(d[13]), "=f"(d[14]), "=f"(d[15])
    : "r"(a0), "r"(a1), "r"(a2), "r"(a3), "l"(db), "n"(TB));
}
template<int TB> DEVI void wgmma_rs_n64(float (&d)[32], uint32_t a0, uint32_t a1, uint32_t a2, uint32_t a3, uint64_t db, int sd){
  asm volatile("{\n.reg .pred p;\nsetp.ne.b32 p, %37, 0;\n"
    "wgmma.mma_async.sync.aligned.m64n64k16.f32.bf16.bf16 {%0, %1, %2, %3, %4, %5, %6, %7, %8, %9, %10, %11, %12, %13, %14, %15, %16, %17, %18, %19, %20, %21, %22, %23, %24, %25, %26, %27, %28, %29, %30, %31}, {%32,%33,%34,%35}, %36, p, 1, 1, %38;\n}\n"
    : "+f"(d[0]), "+f"(d[1]), "+f"(d[2]), "+f"(d[3]), "+f"(d[4]), "+f"(d[5]), "+f"(d[6]), "+f"(d[7]), "+f"(d[8]), "+f"(d[9]), "+f"(d[10]), "+f"(d[11]), "+f"(d[12]), "+f"(d[13]), "+f"(d[14]), "+f"(d[15]), "+f"(d[16]), "+f"(d[17]), "+f"(d[18]), "+f"(d[19]), "+f"(d[20]), "+f"(d[21]), "+f"(d[22]), "+f"(d[23]), "+f"(d[24]), "+f"(d[25]), "+f"(d[26]), "+f"(d[27]), "+f"(d[28]), "+f"(d[29]), "+f"(d[30]), "+f"(d[31])
    : "r"(a0), "r"(a1), "r"(a2), "r"(a3), "l"(db), "r"(sd), "n"(TB));
}
template<int TB> DEVI void wgmma_rs_n64z(float (&d)[32], uint32_t a0, uint32_t a1, uint32_t a2, uint32_t a3, uint64_t db){
  asm volatile("{\n.reg .pred p;\nsetp.ne.b32 p, 0, 0;\n"
    "wgmma.mma_async.sync.aligned.m64n64k16.f32.bf16.bf16 {%0, %1, %2, %3, %4, %5, %6, %7, %8, %9, %10, %11, %12, %13, %14, %15, %16, %17, %18, %19, %20, %21, %22, %23, %24, %25, %26, %27, %28, %29, %30, %31}, {%32,%33,%34,%35}, %36, p, 1, 1, %37;\n}\n"
    : "=f"(d[0]), "=f"(d[1]), "=f"(d[2]), "=f"(d[3]), "=f"(d[4]), "=f"(d[5]), "=f"(d[6]), "=f"(d[7]), "=f"(d[8]), "=f"(d[9]), "=f"(d[10]), "=f"(d[11]), "=f"(d[12]), "=f"(d[13]), "=f"(d[14]), "=f"(d[15]), "=f"(d[16]), "=f"(d[17]), "=f"(d[18]), "=f"(d[19]), "=f"(d[20]), "=f"(d[21]), "=f"(d[22]), "=f"(d[23]), "=f"(d[24]), "=f"(d[25]), "=f"(d[26]), "=f"(d[27]), "=f"(d[28]), "=f"(d[29]), "=f"(d[30]), "=f"(d[31])
    : "r"(a0), "r"(a1), "r"(a2), "r"(a3), "l"(db), "n"(TB));
}

__device__ __align__(1024) bf16 g_q[32*2048*32];
__device__ __align__(1024) bf16 g_kvb[32*16*2*128*32];
__device__ __align__(1024) bf16 g_o[2048*2048];
__device__ __align__(16) float g_kv[2*32*64*40];
__device__ __align__(1024) uint4 g_kvi[8*1280];
__device__ __align__(16) unsigned g_cnt[192];
__device__ unsigned g_tile[32*16];
__device__ unsigned g_epoch;
__device__ float g_gate[2048];
constexpr int C_KV=0, C_KI=8, C_OA=16, C_OB=32, C_G=96, C_OP=128;

constexpr float LOG2E = 1.4426950408889634f;
constexpr float SC = 0.17677669529663687f*LOG2E;
constexpr float OFFS = 88.f;
constexpr uint32_t HI64 = (512u>>4)|(2u<<30);
constexpr uint32_t HI128 = (1024u>>4)|(1u<<30);
constexpr uint32_t SB = 1024;

#define RAV 144
#define RGV 200
#define PAV 4
#define PARTV 12
#define NPRE 2
#define NSL 100
#define HP 30
namespace k2 {
  constexpr int NST=4, GST=4;
  constexpr uint32_t SQ=SB, SKV=SQ+16384, SG=SKV+NST*16384, SW=SG+GST*32768, SO=SW+8192, SONES=SO+8192, SGATE=SONES+1024, BARS=SGATE+512;
  constexpr uint32_t B_KF=BARS, B_KE=BARS+32, B_Q=BARS+64, B_W=BARS+80, B_GF=BARS+128, B_GE=BARS+192, B_PF=BARS+256, B_PE=BARS+320, B_E=BARS+96, B_X=BARS+104, B_O=BARS+112, B_D=BARS+120, SEP=BARS+384;
  constexpr uint32_t PST=49152, PR=SQ;
  constexpr uint32_t SMEM=BARS+512-SB;
  constexpr int RA=RAV, RG=RGV, RP=512-2*RAV-RGV;
  constexpr int PA=PAV, PART=PARTV;
}
struct Maps { CUtensorMap x, wa, go, gos, woa, wob, out, wphi, wb; const bf16 *xp, *gw; };

DEVI void mnmx(const float (&p)[16], float& x0, float& x1, float& n0, float& n1){
  x0=fmaxf(p[0],p[1]); n0=fminf(p[0],p[1]); x1=fmaxf(p[2],p[3]); n1=fminf(p[2],p[3]);
  #pragma unroll
  for(int j=1;j<4;j++){ x0=fmaxf(x0,fmaxf(p[4*j],p[4*j+1])); n0=fminf(n0,fminf(p[4*j],p[4*j+1])); x1=fmaxf(x1,fmaxf(p[4*j+2],p[4*j+3])); n1=fminf(n1,fminf(p[4*j+2],p[4*j+3])); }
  #pragma unroll
  for(int o=1;o<4;o<<=1){ x0=fmaxf(x0,__shfl_xor_sync(0xffffffffu,x0,o)); x1=fmaxf(x1,__shfl_xor_sync(0xffffffffu,x1,o));
                          n0=fminf(n0,__shfl_xor_sync(0xffffffffu,n0,o)); n1=fminf(n1,__shfl_xor_sync(0xffffffffu,n1,o)); }
}

__global__ void __launch_bounds__(512,1) k_main(const __grid_constant__ Maps mp){
  using namespace k2;
  extern __shared__ __align__(1024) uint8_t smem_raw[];
  const uint32_t cb=smem_u32(smem_raw)-SB;
  if(cb&0xffffffu) asm volatile("trap;");
  const uint32_t B_KF=cb+k2::B_KF, B_KE=cb+k2::B_KE, B_Q=cb+k2::B_Q, B_W=cb+k2::B_W, B_GF=cb+k2::B_GF, B_GE=cb+k2::B_GE, SGATE=cb+k2::SGATE,
                 B_PF=cb+k2::B_PF, B_PE=cb+k2::B_PE, B_E=cb+k2::B_E, B_X=cb+k2::B_X, B_O=cb+k2::B_O, B_D=cb+k2::B_D, SEP=cb+k2::SEP;
  const int tid=threadIdx.x, lane=tid&31, warp=__shfl_sync(0xffffffffu,tid>>5,0);
  const int m=blockIdx.x&15, hh=blockIdx.x>>4;
  if(tid==0){
    for(int s=0;s<NST;s++){ mbar_init(B_KF+8*s,1); mbar_init(B_KE+8*s,8); }
    for(int s=0;s<GST;s++){ mbar_init(B_GF+8*s,1); mbar_init(B_GE+8*s,8); }
    mbar_init(B_E,1); mbar_init(B_X,1); mbar_init(B_O,1); mbar_init(B_D,8);
    mbar_init(B_Q,1); mbar_init(B_Q+8,1); mbar_init(B_W,1); mbar_init(B_W+8,1);
    asm volatile("fence.mbarrier_init.release.cluster;":::"memory"); }
  if(tid==416){
    for(int s=0;s<4;s++){ mbar_init(B_PF+8*s,1); mbar_init(B_PE+8*s,16); }
    asm volatile("fence.mbarrier_init.release.cluster;":::"memory"); fence_async_smem();
    for(int s=0;s<4;s++){ const uint32_t a=cb+PR+s*PST; mbar_expect_tx(B_PF+8*s,PST); tma2d(a,&mp.x,s*64,m*128,B_PF+8*s);
      if(s<NPRE) for(int b=0;b<4;b++) tma2d(a+16384+b*8192,&mp.wb,(b<3 ? b*1024 : 2112)+hh*128,s*64,B_PF+8*s); }
  }
  if(tid<256) asm volatile("st.shared.u32 [%0], %1;"::"r"(cb+SONES+tid*4),"r"(0x3F803F80u):"memory");
  cluster_sync();
  auto epoch=[&]{ mbar_wait(B_E,0); uint32_t e; asm volatile("ld.shared.u32 %0, [%1];":"=r"(e):"r"(SEP):"memory"); return e; };

  if(warp>=12){
    reg_dealloc<RP>();
    if(warp==12){
      const uint32_t tag=epoch();
      bar_sync(3,288);
      if(lane==0){
        const uint32_t pr=(m&1)^1;
        mbar_arrive_cl(mapa(B_X,pr));
        mbar_arrive(B_KF); mbar_expect_tx(B_KF+8,16384);
        mbar_wait(B_X,0);
        asm volatile("cp.async.bulk.shared::cluster.shared::cta.mbarrier::complete_tx::bytes [%0], [%1], %2, [%3];"::"r"(mapa(cb+SKV+16384,pr)),"r"(cb+SKV),"r"(16384),"r"(mapa(B_KF+8,pr)):"memory");
        bulk_s2g(g_kvb+((size_t)(4*hh+1)*16+m)*8192, cb+SKV+3*16384, 16384);
        bulk_commit();
      }
      uint32_t ready=0;
      #pragma unroll 1
      for(int it=2;it<64;it++){ const int h=4*hh+(it>>4), t=(it+(m&14))&15, sl=it&3;
        if((it&15)==0) ready=0;
        if(!((ready>>t)&1)){
          for(int i=0;;i++){ unsigned v; asm volatile("ld.relaxed.gpu.global.u32 %0, [%1];":"=r"(v):"l"(&g_tile[h*16+(lane&15)]):"memory");
            ready=__ballot_sync(0xffffffffu, v==tag); if((ready>>t)&1) break; if(i>(1<<22)) asm volatile("trap;"); __nanosleep(NSL); }
          asm volatile("fence.acq_rel.cta;":::"memory"); fence_async_all();
          }
        if(lane==0){
          if(it==3) bulk_wait_read<0>();
          if(it==4){ flag_wait_eq(&g_tile[(4*hh)*16+m],tag);
            mbar_wait(B_KF+8,0); mbar_arrive_cl(mapa(B_X,(m&1)^1));
            mbar_wait(B_X,1); }
          mbar_wait(B_KE+8*sl,((it>>2)&1)^1); mbar_expect_tx(B_KF+8*sl,16384);
          bulk_g2s(cb+SKV+sl*16384, g_kvb+((size_t)h*16+t)*8192, 16384, B_KF+8*sl);
          if(it==3){
            #pragma unroll
            for(int i=0;i<8;i++) mbar_arrive_cl(mapa(B_GE+24,i&1)); }
          if(it==9) flag_wait_eq(&g_tile[(4*hh)*16+(m^1)],tag);
          if(it==5){
            #pragma unroll
            for(int j=0;j<2;j++) bulk_s2g(g_kvb+((size_t)(4*hh+2+j)*16+m)*8192+4096, cb+SW+j*8192, 8192);
            bulk_commit(); }
          if(it==7){ bulk_wait<0>(); flag_set_rlx(&g_tile[(4*hh+1)*16+m],tag); mbar_expect_tx(B_W,8192); tma2d(cb+SW,&mp.wphi,0,hh*128,B_W); }
          if(it==16+NST || it==32+NST){ const int r=(it>>4)&1^1;
            flag_wait_eq(&g_tile[(h+1)*16+m],tag); fence_async_all();
            mbar_expect_tx(B_Q+8*r,8192); bulk_g2s(cb+SQ+r*8192, g_q+((size_t)(h+1)*2048+m*128)*32, 8192, B_Q+8*r); } }
        __syncwarp(); }
    } else if(warp==13){
      if(lane==0){
        const uint32_t rank=m&1;
        #pragma unroll 1
        for(int it=NPRE;it<16;it++){ const int s=it&3, k=it*64; const uint32_t a=cb+PR+s*PST, bar=B_PF+8*s;
          if(it>=4){ mbar_wait(B_PE+8*s,((it>>2)&1)^1); mbar_expect_tx(bar,PST); tma2d(a,&mp.x,k,m*128,bar); }
          tma2d_mc(a+16384+rank*16384,&mp.wb,rank*2048+hh*128,k,bar,3);
          tma2d_mc(a+24576+rank*16384,&mp.wb,(rank ? 2112 : 1024)+hh*128,k,bar,3); }
        const uint32_t tag=epoch();
        #pragma unroll 1
        for(int it=0;it<93;it++){
          const int j=it-65, s = it<65 ? it&3 : j<3 ? (j+1)%3 : j&3; const uint32_t a=cb+SG+s*32768, bar=B_GF+8*s;
          mbar_wait(B_GE+8*s, it<65 ? (it>>2)&1 : ((j>>2)^(s==0))&1);
          if(it<64){
            const int job=it>>4, k=(it&15)*64, n = job==0 ? rank*1024+hh*128+64 : job<3 ? 1024+rank*1024+hh*128+(job-1)*64 : hh*128+rank*64;
            mbar_expect_tx(bar,32768); tma2d_mc(a+16384+rank*8192,job==0 ? &mp.wb : &mp.wa,n,k,bar,3); tma2d(a,&mp.x,k,m*128,bar);
          } else if(it==64){
            flag_wait(&g_cnt[C_KI+hh],16*tag); fence_async_all();
            mbar_expect_tx(bar,20480); bulk_g2s(a,g_kvi+hh*1280,20480,bar);
          } else {
            const int k = j<8 ? 1024+j*64 : j<24 ? (j-8)*64 : 1024+(j-16)*64;
            mbar_expect_tx(bar,32768);
            if(k<1024) tma2d_mc(a+16384+rank*8192,&mp.woa,hh*128+rank*64,k,bar,3);
            else tma4d_mc(a+16384+rank*8192,&mp.wob,hh*128+rank*64,0,(k-1024)>>8,(k&255)>>5,bar,3);
            if(k==0){ flag_wait(&g_cnt[C_OA+m],8*tag); fence_async_all(); }
            if(k>=1024 && (k&255)==0){ flag_wait(&g_cnt[C_OB+((k-1024)>>8)*16+m],8*tag); fence_async_all(); }
            tma2d(a,&mp.go,k,m*128,bar);
          } }
        uint32_t todo=15, rdy=0;
        #pragma unroll 1
        for(int it=93;it<97;it++){
          const int s=it-93; const uint32_t a=cb+SG+s*32768, bar=B_GF+8*s;
          mbar_wait(B_GE+8*s,s!=0);
          if(!rdy){
          for(int i=0;!rdy;i++){ uint32_t c0,c1,c2,c3;
            asm volatile("ld.relaxed.gpu.global.v4.u32 {%0,%1,%2,%3}, [%4];":"=r"(c0),"=r"(c1),"=r"(c2),"=r"(c3):"l"(&g_cnt[C_OP+4*m]):"memory");
            rdy=todo&((c0==2*tag)|(c1==2*tag)<<1|(c2==2*tag)<<2|(c3==2*tag)<<3);
            if(i>(1<<22)) asm volatile("trap;"); }
          asm volatile("fence.acq_rel.cta;":::"memory"); fence_async_all(); }
          const int p=__ffs(rdy)-1; todo&=~(1u<<p); rdy&=~(1u<<p);
          mbar_expect_tx(bar,32768);
          tma2d(a,&mp.go,1792+p*64,m*128,bar);
          tma4d(a+16384,&mp.wob,hh*128,0,3,2*p,bar); tma4d(a+24576,&mp.wob,hh*128+64,0,3,2*p,bar);
 }
      }
    } else if(warp==14){
      const uint32_t tag=epoch();
      bar_sync(6,288);
      if(lane==0){ bulk_s2g(g_kvb+((size_t)(4*hh)*16+m)*8192, cb+SKV, 16384); bulk_commit(); bulk_wait<0>();
        flag_set_rlx(&g_tile[(4*hh)*16+m],tag);
        flag_wait(&g_cnt[C_G+m],8*tag); }
      __syncwarp();
      #pragma unroll
      for(int i=0;i<4;i++) asm volatile("st.shared.f32 [%0], %1;"::"r"(SGATE+(i*32+lane)*4),"f"(__ldcg(g_gate+m*128+i*32+lane)):"memory");
      __syncwarp(); if(lane==0) mbar_arrive(B_W+8);
      for(int r=0;r<4;r++){ bar_sync(2,288);
        if(lane==0){ tma2d_store(&mp.gos,cb+SO,1024+r*256+hh*32,m*128); bulk_commit(); bulk_wait<0>();
          flag_add_rlx(&g_cnt[r<3 ? C_OB+r*16+m : C_OP+4*m+(hh>>1)]); mbar_arrive(B_O); }
        __syncwarp(); }
    } else {
      const uint32_t tag=ld_acq(&g_epoch)+1;
      if(lane==0){ asm volatile("st.shared.u32 [%0], %1;"::"r"(SEP),"r"(tag):"memory"); mbar_arrive(B_E); }
      #pragma unroll
      for(int i=0;i<5;i++) *(float4*)(g_kv+((tag+1)&1)*81920+blockIdx.x*640+i*128+lane*4)=make_float4(0.f,0.f,0.f,0.f);
      if(lane==0) flag_wait_eq(&g_tile[(4*hh+1)*16+m],tag);
      bar_sync(4,160);
      if(lane==0){
        #pragma unroll
        for(int j=0;j<2;j++){ bulk_s2g(g_q+((size_t)(4*hh+2+j)*2048+m*128)*32, cb+SG+3*32768+j*8192, 8192); bulk_s2g(g_kvb+((size_t)(4*hh+2+j)*16+m)*8192, cb+SG+3*32768+16384+j*8192, 8192); }
        bulk_commit(); bulk_wait_read<0>(); }
      __syncwarp();
      if(lane<8) mbar_arrive_cl(mapa(B_GE+24,lane&1));
      if(lane==0){ bulk_wait<0>(); flag_set_rlx(&g_tile[(4*hh+2)*16+m],tag); flag_set_rlx(&g_tile[(4*hh+3)*16+m],tag); }
      bar_sync(4,160);
      if(lane==0){ flag_add(&g_cnt[C_KV+hh]); flag_wait(&g_cnt[C_KV+hh],16*tag); }
      __syncwarp();
      const int f=m*16+(lane>>1), c0=(lane&1)*2; const float* src=g_kv+(tag&1)*81920+((size_t)hh*256+f)*40;
      #pragma unroll
      for(int c=c0;c<c0+2;c++){ const float4 a=__ldcg((const float4*)(src+c*8)), b=__ldcg((const float4*)(src+c*8+4));
        g_kvi[hh*1280+f*4+(c^((f>>1)&3))]=make_uint4(pack(a.x,a.y),pack(a.z,a.w),pack(b.x,b.y),pack(b.z,b.w)); }
      if((lane&1)==0) g_kvi[hh*1280+1024+(f&63)*4+((f>>6)^((f>>1)&3))]=make_uint4(pack(__ldcg(src+32),1.f),0u,0u,0u);
      __syncwarp();
      if(lane==0){ flag_add(&g_cnt[C_KI+hh]); }
      bar_sync(4,160);
      if(lane==0){ tma2d_store(&mp.go,cb+SG+3*32768,hh*128,m*128); tma2d_store(&mp.go,cb+SG+3*32768+16384,hh*128+64,m*128); bulk_commit(); bulk_wait_read<0>(); }
      __syncwarp();
      if(lane<8) mbar_arrive_cl(mapa(B_GE+24,lane&1));
      if(lane==0){ bulk_wait<0>(); flag_add_rlx(&g_cnt[C_OA+m]); }
    }
  } else if(warp>=8){
    const int wq=warp-8, t128=tid-256;
    uint32_t zz; asm volatile("mov.u32 %0, 0;":"=r"(zz)); zz=__shfl_sync(0xffffffffu,zz,0);
    uint32_t ph=0;
    const uint32_t rel=mapa(B_GE,lane&1);
    auto release=[&](int slot){ if(lane<2) mbar_arrive_cl(rel+8*slot); };
    const int srow=wq*16+(lane&15);
    {
      #pragma unroll 1
      for(int r=0;r<4;r++){ const int row=m*128+hh*16+wq*4+r; float gs=0;
        #pragma unroll
        for(int j=0;j<4;j++){ const uint4 a=__ldg((const uint4*)(mp.xp+(size_t)row*1024+j*256+lane*8)), b=__ldg((const uint4*)(mp.gw+j*256+lane*8));
          const __nv_bfloat162* pa=(const __nv_bfloat162*)&a; const __nv_bfloat162* pb=(const __nv_bfloat162*)&b;
          #pragma unroll
          for(int e=0;e<4;e++){ float2 p=__bfloat1622float2(__hmul2(pa[e],pb[e])); gs+=p.x+p.y; } }
        #pragma unroll
        for(int o=16;o;o>>=1) gs+=__shfl_xor_sync(0xffffffffu,gs,o);
        gs=__bfloat162float(__float2bfloat16(gs));
        if(lane==0) g_gate[row]=__bfloat162float(__float2bfloat16(1.f/(1.f+__expf(-gs)))); }
      bar_sync(1,128);
      if(t128==0) flag_add(&g_cnt[C_G+m]);
      bar_sync(5,384);
      #pragma unroll
      for(int i=0;i<3;i++) release(i);
    }
    reg_alloc<RG>();
    #pragma unroll 1
    for(int job=-1;job<4;job++){
      float acc[2][64];
      #pragma unroll
      for(int i=0;i<64;i++){ acc[0][i]=0.f; acc[1][i]=0.f; }
      fence_regs(acc[0]); fence_regs(acc[1]);
      const int ng = job==3 ? 8 : 4;
      #pragma unroll 1
      for(int g=0;g<ng;g++){
        #pragma unroll
        for(int c=0;c<4;c++){
          if(c==(HP&3) && g==7) mbar_wait(B_D,0);
          mbar_wait(B_GF+8*c, c==0 ? ph^(job==3) : ph);
          const uint32_t ad=((SG+c*32768)>>4)|(1u<<16), bd=((SG+c*32768+16384)>>4)|((8192u>>4)<<16);
          #pragma unroll
          for(int kk=0;kk<4;kk++){ const int sd=1;
            wg_fence();
            wgmma_ss_n128<0,1>(acc[0],mk_desc2(ad+kk*2,HI128),mk_desc2(bd+kk*128,HI128),sd);
            wgmma_ss_n128<0,1>(acc[1],mk_desc2(ad+512+kk*2,HI128),mk_desc2(bd+kk*128,HI128),sd);
            wg_commit(); wg_wait<1>();
            if(kk==0 && (c==0 ? g>0 : g<7)) release((c+3)&3); }
        }
        ph^=1; }
      wg_wait<0>();
      bar_sync(1,128);
      const uint32_t SCR = SG + (job<2 ? 3*32768 : 0);
      fence_regs(acc[0]); fence_regs(acc[1]);
      if(job<0){
        #pragma unroll
        for(int mb=0;mb<2;mb++){ const int row=mb*64+srow;
          #pragma unroll
          for(int c=0;c<8;c++){ const float* v=&acc[mb][8*c];
            stsm4(cb+SCR+(c>>1)*8192+row*64+((((c&1)*2+(lane>>4))^((row>>1)&3))<<4), pack(v[0],v[1]),pack(v[2],v[3]),pack(v[4],v[5]),pack(v[6],v[7])); } }
        fence_async_smem(); bar_arrive(4,160);
      } else if(job<2){
        if(job==0) mbar_wait(B_W,0);
        uint32_t kf[2][16];
        #pragma unroll
        for(int mb=0;mb<2;mb++){
          #pragma unroll
          for(int i=0;i<16;i++) kf[mb][i]=pack(acc[mb][2*i],acc[mb][2*i+1]);
          const int row=mb*64+srow;
          #pragma unroll
          for(int c=0;c<4;c++){ const float* v=&acc[mb][32+8*c];
            stsm4(cb+SCR+(c>>1)*8192+row*64+((((c&1)*2+(lane>>4))^((row>>1)&3))<<4), pack(v[0],v[1]),pack(v[2],v[3]),pack(v[4],v[5]),pack(v[6],v[7])); }
        }
        float pk[2][2][16];
        wg_fence();
        #pragma unroll
        for(int h=0;h<2;h++){ const uint32_t wd=((SW+(job*2+h)*2048)>>4)|(1u<<16);
          #pragma unroll
          for(int mb=0;mb<2;mb++){
            wgmma_rs_n32z<1>(pk[h][mb],kf[mb][8*h],kf[mb][8*h+1],kf[mb][8*h+2],kf[mb][8*h+3],mk_desc2(wd,HI64));
            wgmma_rs_n32<1>(pk[h][mb],kf[mb][8*h+4],kf[mb][8*h+5],kf[mb][8*h+6],kf[mb][8*h+7],mk_desc2(wd+64,HI64),1); } }
        wg_commit(); wg_wait<0>();
        float kv[20];
        auto put_kv=[&](int h){
          wg_wait<0>(); fence_regs(kv);
          float* dst=g_kv+(epoch()&1)*81920+((size_t)(4*hh+2*job+h)*64+wq*16+(lane>>2))*40+(lane&3)*2;
          #pragma unroll
          for(int j=0;j<4;j++){ red2(dst+8*j,kv[4*j],kv[4*j+1]); red2(dst+320+8*j,kv[4*j+2],kv[4*j+3]); }
          if((lane&3)==0){ red1(dst+32,kv[16]); red1(dst+352,kv[18]); } };
        #pragma unroll
        for(int h=0;h<2;h++){
          fence_regs(pk[h][0]); fence_regs(pk[h][1]);
          uint32_t ph_[2][16];
          #pragma unroll
          for(int mb=0;mb<2;mb++){
            float (&p)[16]=pk[h][mb]; float x0,x1,n0,n1; mnmx(p,x0,x1,n0,n1);
            x0*=-LOG2E; x1*=-LOG2E; n0*=LOG2E; n1*=LOG2E;
            float ep[16],en[16],sp0=0,sp1=0,sn0=0,sn1=0;
            #pragma unroll
            for(int i=0;i<16;i++){ const bool hi=i&2; ep[i]=ex2(fmaf(p[i],LOG2E,hi?x1:x0)); en[i]=ex2(fmaf(p[i],-LOG2E,hi?n1:n0));
              if(hi){ sp1+=ep[i]; sn1+=en[i]; } else { sp0+=ep[i]; sn0+=en[i]; } }
            #pragma unroll
            for(int o=1;o<4;o<<=1){ sp0+=__shfl_xor_sync(0xffffffffu,sp0,o); sp1+=__shfl_xor_sync(0xffffffffu,sp1,o); sn0+=__shfl_xor_sync(0xffffffffu,sn0,o); sn1+=__shfl_xor_sync(0xffffffffu,sn1,o); }
            sp0=rcp(sp0); sp1=rcp(sp1); sn0=rcp(sn0); sn1=rcp(sn1);
            #pragma unroll
            for(int i=0;i<8;i++){ const bool hi=i&1; ph_[mb][i]=pack(ep[2*i]*(hi?sp1:sp0),ep[2*i+1]*(hi?sp1:sp0)); ph_[mb][8+i]=pack(en[2*i]*(hi?sn1:sn0),en[2*i+1]*(hi?sn1:sn0)); }
          }
          if(h==1){
            #pragma unroll
            for(int i=0;i<16;i++) asm volatile(""::"r"(ph_[0][i]),"r"(ph_[1][i]));
            put_kv(0); bar_sync(1,128); }
          #pragma unroll
          for(int mb=0;mb<2;mb++){ const int row=mb*64+srow;
            #pragma unroll
            for(int c=0;c<4;c++) stsm4(cb+SCR+16384+row*128+(((2*c+(lane>>4))^(row&7))<<4), ph_[mb][4*c],ph_[mb][4*c+1],ph_[mb][4*c+2],ph_[mb][4*c+3]); }
          fence_async_smem(); bar_sync(1,128);
          const uint32_t pd=((SCR+16384)>>4)|(1u<<16), vd=((SCR+h*8192)>>4)|(((SONES-SCR-h*8192)>>4)<<16);
          wg_fence();
          wgmma_ss_n40z<1,1>(kv,mk_desc2(pd,HI128),mk_desc2(vd,HI64));
          #pragma unroll
          for(int ks=1;ks<8;ks++) wgmma_ss_n40<1,1>(kv,mk_desc2(pd+ks*128,HI128),mk_desc2(vd+ks*(64u-(64u<<16)),HI64),1);
          wg_commit();
        }
        put_kv(1);
        release(3);
        if(job==1) bar_arrive(4,160);
      } else if(job==2){
        uint32_t qf[2][32];
        #pragma unroll
        for(int mb=0;mb<2;mb++){
          #pragma unroll
          for(int i=0;i<32;i++) qf[mb][i]=pack(acc[mb][2*i],acc[mb][2*i+1]); }
        float pq[2][16], op[20], on[20]; uint32_t e[2][16];
        auto PQ=[&](const int i){ const int h=i>>1, mb=i&1; const uint32_t wd=((SW+h*2048)>>4)|(1u<<16);
          wgmma_rs_n32z<1>(pq[mb],qf[mb][8*h],qf[mb][8*h+1],qf[mb][8*h+2],qf[mb][8*h+3],mk_desc2(wd,HI64));
          wgmma_rs_n32<1>(pq[mb],qf[mb][8*h+4],qf[mb][8*h+5],qf[mb][8*h+6],qf[mb][8*h+7],mk_desc2(wd+64,HI64),1); };
        auto EX=[&](const int b){
          float (&p)[16]=pq[b]; fence_regs(p); float x0,x1,n0,n1; mnmx(p,x0,x1,n0,n1);
          x0*=-LOG2E; x1*=-LOG2E; n0*=LOG2E; n1*=LOG2E;
          #pragma unroll
          for(int i=0;i<8;i++){ const bool hi=i&1;
            e[b][i]=pack(ex2(fmaf(p[2*i],LOG2E,hi?x1:x0)),ex2(fmaf(p[2*i+1],LOG2E,hi?x1:x0)));
            e[b][8+i]=pack(ex2(fmaf(p[2*i],-LOG2E,hi?n1:n0)),ex2(fmaf(p[2*i+1],-LOG2E,hi?n1:n0))); }
          #pragma unroll
          for(int i=0;i<16;i++) asm volatile(""::"r"(e[b][i])); };
        wg_fence(); PQ(0); PQ(1); wg_commit(); wg_wait<0>();
        EX(0);
        mbar_wait(B_GF,ph); mbar_wait(B_W+8,0);
        float gt[4];
        #pragma unroll
        for(int i=0;i<4;i++) asm volatile("ld.shared.f32 %0, [%1];":"=f"(gt[i]):"r"(SGATE+((i>>1)*64+(i&1)*8+wq*16+(lane>>2))*4));
        #pragma unroll
        for(int i=0;i<8;i++){ const int h=i>>1, mb=i&1;
          const uint32_t kd=((SCR+h*4096)>>4)|(((16384+16*h-h*4096)>>4)<<16);
          wg_fence();
          wgmma_rs_n40z<1>(op,e[mb][0],e[mb][1],e[mb][2],e[mb][3],mk_desc2(kd,HI64));
          wgmma_rs_n40<1>(op,e[mb][4],e[mb][5],e[mb][6],e[mb][7],mk_desc2(kd+64,HI64),1);
          wgmma_rs_n40z<1>(on,e[mb][8],e[mb][9],e[mb][10],e[mb][11],mk_desc2(kd+128,HI64));
          wgmma_rs_n40<1>(on,e[mb][12],e[mb][13],e[mb][14],e[mb][15],mk_desc2(kd+192,HI64),1);
          if(i<6) PQ(i+2);
          wg_commit();
          if(i<7) EX(mb^1);
          BOUND(40+i);
          wg_wait<0>(); fence_regs(op); fence_regs(on);
          float a0=rcp(op[17]), b0=rcp(on[17]), a1=rcp(op[19]), b1=rcp(on[19]);
          const float f0=__fdividef(gt[2*mb],op[16]*a0+on[16]*b0+1e-6f), f1=__fdividef(gt[2*mb+1],op[18]*a1+on[18]*b1+1e-6f);
          a0=__shfl_sync(0xffffffffu,a0*f0,lane&28); b0=__shfl_sync(0xffffffffu,b0*f0,lane&28);
          a1=__shfl_sync(0xffffffffu,a1*f1,lane&28); b1=__shfl_sync(0xffffffffu,b1*f1,lane&28);
          const int row=mb*64+srow;
          #pragma unroll
          for(int c=0;c<2;c++){ const float* p=&op[8*c]; const float* n=&on[8*c];
            stsm4(cb+SG+3*32768+(h>>1)*16384+row*128+((((h&1)*4+c*2+(lane>>4))^(row&7))<<4),
                  pack(p[0]*a0+n[0]*b0,p[1]*a0+n[1]*b0),pack(p[2]*a1+n[2]*b1,p[3]*a1+n[3]*b1),pack(p[4]*a0+n[4]*b0,p[5]*a0+n[5]*b0),pack(p[6]*a1+n[6]*b1,p[7]*a1+n[7]*b1)); }
        }
        fence_async_smem();
        release(0);
        bar_arrive(4,160);
      } else {
        #pragma unroll
        for(int mb=0;mb<2;mb++){ const int row=mb*64+srow;
          #pragma unroll
          for(int c=0;c<8;c++){ const float* v=&acc[mb][8*c];
            stsm4(cb+SCR+(c>>2)*16384+row*128+((((c&3)*2+(lane>>4))^(row&7))<<4), pack(v[0],v[1]),pack(v[2],v[3]),pack(v[4],v[5]),pack(v[6],v[7])); } }
        fence_async_smem(); bar_sync(1,128);
        if(t128==0){ tma2d_store(&mp.out,cb+SCR,hh*128,m*128); tma2d_store(&mp.out,cb+SCR+16384,hh*128+64,m*128); bulk_commit();
          if(blockIdx.x==0) g_epoch=epoch();
          bulk_wait_read<0>(); }
      }
    }
  } else {
    reg_alloc<168>();
    constexpr uint32_t kd0=(SKV>>4)|(1u<<16), vd0=((SKV+8192)>>4)|(((SONES-SKV-8192)>>4)<<16);
    {
      const uint32_t prel=mapa(B_PE,lane&1); const int row=warp*16+(lane&15);
      const uint32_t so=cb+row*64, sx=(row>>1)&3;
      float acc[2][64];
      auto pa=[&](const int k, const bool z){
        const int ps=k&3;
        mbar_wait(B_PF+8*ps,(k>>2)&1);
        const uint32_t ad=((PR+ps*PST+(warp>>2)*8192)>>4)|(1u<<16), bd=((PR+ps*PST+16384)>>4)|((8192u>>4)<<16);
        wg_fence();
        #pragma unroll
        for(int kk=0;kk<4;kk++){
          #pragma unroll
          for(int nb=0;nb<2;nb++){
            if(z&&kk==0) wgmma_ss_n128z<0,1>(acc[nb],mk_desc2(ad,HI128),mk_desc2(bd+nb*1024,HI128));
            else wgmma_ss_n128<0,1>(acc[nb],mk_desc2(ad+kk*2,HI128),mk_desc2(bd+nb*1024+kk*128,HI128),1); }
          if(kk==0){ wg_commit(); wg_wait<1>(); if(!z && k<13 && lane<2) mbar_arrive_cl(prel+8*((k+3)&3)); wg_fence(); } }
        wg_commit(); };
      pa(0,true);
      #pragma unroll 1
      for(int k=1;k<16;k++) pa(k,false);
      wg_wait<0>(); fence_regs(acc[0]); fence_regs(acc[1]);
      bar_sync(5,384);
      auto put=[&](const int c){ const float* v=&acc[c>>3][8*(c&7)]; const int j=(c>>1)&1, bx=c>>2;
        stsm4(so+(bx==0 ? SQ+j*8192 : bx<3 ? SKV+j*49152+(bx-1)*8192 : SW+j*8192)+((((c&1)*2+(lane>>4))^sx)<<4), pack(v[0],v[1]),pack(v[2],v[3]),pack(v[4],v[5]),pack(v[6],v[7])); };
      put(4); put(5); put(8); put(9);
      fence_async_smem(); bar_arrive(6,288);
      put(0); put(1); put(2); put(3); put(6); put(7); put(10); put(11); put(12); put(13); put(14); put(15);
      fence_async_smem(); bar_sync(3,288);
    }
    reg_dealloc<RA>();
    float o[20], S0[32], S1[32], nb0=0, nb1=0; uint32_t P0[16], P1[16];
    #pragma unroll
    for(int i=0;i<20;i++) o[i]=0;
    #pragma unroll
    for(int i=0;i<16;i++) P1[i]=0;
    fence_regs(o);
    uint32_t qf[8];
    auto ldq=[&](int u){ uint32_t t; asm volatile("mov.u32 %0, %%tid.x;":"=r"(t));
      const uint32_t row=(t>>5)*16+(t&15), a=cb+SQ+(u&1)*8192+row*64;
      #pragma unroll
      for(int kk=0;kk<2;kk++) asm volatile("ldmatrix.sync.aligned.m8n8.x4.shared.b16 {%0,%1,%2,%3}, [%4];":"=r"(qf[4*kk]),"=r"(qf[4*kk+1]),"=r"(qf[4*kk+2]),"=r"(qf[4*kk+3])
        :"r"(a+(((2*kk+((t>>4)&1))^((row>>1)&3))<<4)):"memory"); };
    ldq(0);
    auto qk=[&](float (&S)[32], uint32_t kd){
      wgmma_rs_n64z<0>(S,qf[0],qf[1],qf[2],qf[3],mk_desc2(kd,HI64));
      wgmma_rs_n64<0>(S,qf[4],qf[5],qf[6],qf[7],mk_desc2(kd+2,HI64),1); };
    wg_fence(); qk(S0,kd0); wg_commit(); wg_wait<0>(); fence_regs(S0);
    auto epi=[&](int r){
      uint32_t cta,t; asm volatile("mov.u32 %0, %%ctaid.x;":"=r"(cta)); asm volatile("mov.u32 %0, %%tid.x;":"=r"(t));
      const int lr=(t>>5)*16+((t&31)>>2), head=4*(cta>>4)+r;
      if(r==0) mbar_wait(B_W+8,0);
      float g0,g1; asm volatile("ld.shared.f32 %0, [%1];":"=f"(g0):"r"(SGATE+lr*4)); asm volatile("ld.shared.f32 %0, [%1];":"=f"(g1):"r"(SGATE+lr*4+32));
      g0=__bfloat162float(__float2bfloat16(1.f-g0)); g1=__bfloat162float(__float2bfloat16(1.f-g1));
      const float f0=__fdividef(g0,o[16]), f1=__fdividef(g1,o[18]);
      if(r>0) mbar_wait(B_O,(r-1)&1);
      float t0=0,t1=0;
      #pragma unroll
      for(int j=0;j<4;j++){ t0+=fabsf(o[4*j])+fabsf(o[4*j+1]); t1+=fabsf(o[4*j+2])+fabsf(o[4*j+3]); }
      { const uint32_t row=(t>>5)*16+(t&15);
        #pragma unroll
        for(int c=0;c<2;c++){ const float* v=&o[8*c];
          stsm4(cb+SO+row*64+(((c*2+((t>>4)&1))^((row>>1)&3))<<4), pack(v[0]*f0,v[1]*f0),pack(v[2]*f1,v[3]*f1),pack(v[4]*f0,v[5]*f0),pack(v[6]*f1,v[7]*f1)); } }
      const unsigned b0=__ballot_sync(0xffffffffu,!(o[16]<1e30f && t0<3e38f)), b1=__ballot_sync(0xffffffffu,!(o[18]<1e30f && t1<3e38f));
      if(b0|b1){
        const int ln=t&31; const uint8_t* kv=(const uint8_t*)(g_kvb+(size_t)head*16*8192);
        #pragma unroll 1
        for(int rr=0;rr<16;rr++){
          if(!(((rr<8?b0:b1)>>((rr&7)*4))&15)) continue;
          const int qrow=(t>>5)*16+rr; const uint32_t qa=cb+SQ+(r&1)*8192+qrow*64;
          auto dot=[&](int key){ float s=0; const uint8_t* kr=kv+(key>>7)*16384+(key&127)*64;
            #pragma unroll 1
            for(int c=0;c<4;c++){ uint4 a=__ldcg((const uint4*)(kr+((c^((key>>1)&3))<<4))), b;
              asm volatile("ld.shared.v4.u32 {%0,%1,%2,%3}, [%4];":"=r"(b.x),"=r"(b.y),"=r"(b.z),"=r"(b.w):"r"(qa+((c^((qrow>>1)&3))<<4)));
              const uint32_t* pa=&a.x; const uint32_t* pb=&b.x;
              #pragma unroll
              for(int e=0;e<4;e++){ s=fmaf(__uint_as_float(pa[e]<<16),__uint_as_float(pb[e]<<16),s); s=fmaf(__uint_as_float(pa[e]&0xffff0000u),__uint_as_float(pb[e]&0xffff0000u),s); } }
            return s; };
          float mx=-INFINITY;
          #pragma unroll 1
          for(int k=ln;k<2048;k+=32) mx=fmaxf(mx,dot(k));
          #pragma unroll
          for(int of=16;of;of>>=1) mx=fmaxf(mx,__shfl_xor_sync(0xffffffffu,mx,of));
          float a=0,l=0;
          #pragma unroll 1
          for(int k0=0;k0<2048;k0+=32){ const float p=ex2((dot(k0+ln)-mx)*SC); l+=p;
            #pragma unroll 1
            for(int j=0;j<32;j++){ const int key=k0+j; const unsigned short vv=__ldcg((const unsigned short*)(kv+(key>>7)*16384+8192+(key&127)*64+(((ln>>3)^((key>>1)&3))<<4)+(ln&7)*2));
              a=fmaf(__shfl_sync(0xffffffffu,p,j),__uint_as_float((uint32_t)vv<<16),a); } }
          #pragma unroll
          for(int of=16;of;of>>=1) l+=__shfl_xor_sync(0xffffffffu,l,of);
          float g; asm volatile("ld.shared.f32 %0, [%1];":"=f"(g):"r"(SGATE+qrow*4));
          g=__bfloat162float(__float2bfloat16(1.f-g));
          __syncwarp();
          asm volatile("st.shared.u16 [%0], %1;"::"r"(cb+SO+qrow*64+(((ln>>3)^((qrow>>1)&3))<<4)+(ln&7)*2),"h"(__bfloat16_as_ushort(__float2bfloat16(a*g/l))):"memory");
        }
      }
      fence_async_smem(); bar_arrive(2,288);
    };
    const bool l0 = lane==0;
    uint32_t zz; asm volatile("mov.u32 %0, 0;":"=r"(zz)); zz=__shfl_sync(0xffffffffu,zz,0);
    uint32_t sp=NST-1, sc=0, sn=1, phn=0;
    auto newmax=[&](float (&S)[32]){
      float m0=S[0],m1=S[2];
      #pragma unroll
      for(int i=0;i<8;i++){ m0=fmaxf(m0,fmaxf(S[4*i],S[4*i+1])); m1=fmaxf(m1,fmaxf(S[4*i+2],S[4*i+3])); }
      m0=fmaxf(m0,__shfl_xor_sync(0xffffffffu,m0,1)); m0=fmaxf(m0,__shfl_xor_sync(0xffffffffu,m0,2));
      m1=fmaxf(m1,__shfl_xor_sync(0xffffffffu,m1,1)); m1=fmaxf(m1,__shfl_xor_sync(0xffffffffu,m1,2));
      nb0=-(m0*SC+OFFS); nb1=-(m1*SC+OFFS); };
    newmax(S0);
    #pragma unroll
    for(int i=0;i<32;i++) S0[i]=fmaf(S0[i],SC,((i>>1)&1)?nb1:nb0);
    auto step=[&](const int r, const int MODE, const int U, float (&S)[32], uint32_t (&P)[16], float (&Sn)[32], uint32_t (&Pp)[16]){
      const bool first=(U==0)&&MODE==1, second=(U==1)&&MODE==1, last=(U==1)&&MODE==2;
      if(second && r>0) epi(r-1);
      if(last){ if(r==1 || r==2) mbar_wait(B_Q+8*((r+1)&1),0); ldq(r+1); }
      const uint32_t vd= U==0 ? vd0+sp*(1024u-(1024u<<16))+4*(64u-(64u<<16)) : vd0+sc*(1024u-(1024u<<16));
      const uint32_t kd= U==0 ? kd0+sc*1024u+256u : kd0+sn*1024u;
      bool ok=true;
      auto ex=[&](const int i){ P[i]=pack(ex2(S[2*i]),ex2(S[2*i+1])); };
      if(U==0 && !(MODE==2 && r==3)) ok=mbar_try(B_KF+8*sn, phn);
      wg_fence();
      qk(Sn,kd); wg_commit();
      #pragma unroll
      for(int kk=0;kk<4;kk++){
        if(second&&kk==0) wgmma_rs_n40z<1>(o,Pp[4*kk],Pp[4*kk+1],Pp[4*kk+2],Pp[4*kk+3],mk_desc2(vd+kk*(64u-(64u<<16)),HI64));
        else wgmma_rs_n40<1>(o,Pp[4*kk],Pp[4*kk+1],Pp[4*kk+2],Pp[4*kk+3],mk_desc2(vd+kk*(64u-(64u<<16)),HI64),1); }
      wg_commit();
      #pragma unroll
      for(int i=0;i<PA;i++) ex(i);
      #pragma unroll
      for(int i=0;i<PA;i++) asm volatile(""::"r"(P[i]));
      if(U==0){ if(__builtin_expect(!ok,0)) mbar_wait(B_KF+8*sn, phn); } else BOUND(1+MODE*8);
      #pragma unroll
      for(int i=PA;i<PART;i++) ex(i);
      #pragma unroll
      for(int i=PA;i<PART;i++) asm volatile(""::"r"(P[i]));
      BOUND(2+U+MODE*8);
      wg_wait<1>(); fence_regs(Sn);
      if(last) newmax(Sn);
      #pragma unroll
      for(int j=0;j<32;j++){
        Sn[j]=fmaf(Sn[j],SC,((j>>1)&1)?nb1:nb0);
        if((j+1)*(16-PART)/32 != j*(16-PART)/32) ex(PART+j*(16-PART)/32); }
      fence_regs(Sn);
      #pragma unroll
      for(int i=PART;i<16;i++) asm volatile(""::"r"(P[i]));
      wg_wait<0>(); fence_regs(o);
      if(U==0){ if(l0 && !(first && r==0)) mbar_arrive(B_KE+8*sp);
      }
      else { sp=sc; sc=sn; sn=sn+1==NST?0:sn+1; phn^=(sn==0); }
    };
    #pragma unroll 1
    for(int r=0;r<4;r++){
      step(r,1,0,S0,P0,S1,P1); step(r,1,1,S1,P1,S0,P0);
      #pragma unroll 1
      for(int t=0;t<14;t++){ step(r,0,0,S0,P0,S1,P1); step(r,0,1,S1,P1,S0,P0); }
      step(r,2,0,S0,P0,S1,P1); step(r,2,1,S1,P1,S0,P0);
    }
    { const uint32_t vd=vd0+sp*(1024u-(1024u<<16))+4*(64u-(64u<<16));
      wg_fence();
      #pragma unroll
      for(int kk=0;kk<4;kk++) wgmma_rs_n40<1>(o,P1[4*kk],P1[4*kk+1],P1[4*kk+2],P1[4*kk+3],mk_desc2(vd+kk*(64u-(64u<<16)),HI64),1);
      wg_commit(); }
    if(l0) mbar_arrive(B_D);
    wg_wait<0>(); fence_regs(o);
    epi(3);
  }
}

typedef CUresult (*PFN_enc)(CUtensorMap*, CUtensorMapDataType, cuuint32_t, void*, const cuuint64_t*, const cuuint64_t*, const cuuint32_t*, const cuuint32_t*, CUtensorMapInterleave, CUtensorMapSwizzle, CUtensorMapL2promotion, CUtensorMapFloatOOBfill);
static CUtensorMap mk_map(PFN_enc fn, const void* p, int rank, const cuuint64_t* dims, const cuuint64_t* strides, const cuuint32_t* box, CUtensorMapSwizzle sw){
  CUtensorMap m; cuuint32_t es[4]={1,1,1,1};
  fn(&m, CU_TENSOR_MAP_DATA_TYPE_BFLOAT16, rank, (void*)p, dims, strides, box, es, CU_TENSOR_MAP_INTERLEAVE_NONE, sw, CU_TENSOR_MAP_L2_PROMOTION_L2_256B, CU_TENSOR_MAP_FLOAT_OOB_FILL_NONE);
  return m; }
static CUtensorMap map2d(PFN_enc fn, const void* p, uint64_t inner, uint64_t outer, uint32_t bi, uint32_t bo, CUtensorMapSwizzle sw){
  cuuint64_t d[2]={inner,outer}, s[1]={inner*2}; cuuint32_t b[2]={bi,bo}; return mk_map(fn,p,2,d,s,b,sw); }

extern "C" void kernel_launch(void* const* d_in, const int* in_sizes, int n_in, void* d_out, int out_size){
  static bool init=false; static Maps mp; static const void* key[8];
  const void* cur[8]={d_in[0],d_in[1],d_in[2],d_in[3],d_in[5],d_in[6],d_in[7],d_out};
  bool same=init; for(int i=0;i<8;i++) same = same && key[i]==cur[i];
  if(!same){
    PFN_enc fn=nullptr; cudaDriverEntryPointQueryResult q; cudaGetDriverEntryPoint("cuTensorMapEncodeTiled",(void**)&fn,cudaEnableDefault,&q);
    void* go; cudaGetSymbolAddress(&go,g_o);
    const CUtensorMapSwizzle S128=CU_TENSOR_MAP_SWIZZLE_128B;
    mp.x=map2d(fn,d_in[0],1024,2048,64,128,S128);
    mp.wa=map2d(fn,d_in[1],3072,1024,64,64,S128);
    mp.wb=map2d(fn,d_in[5],3072,1024,64,64,S128);
    mp.go=map2d(fn,go,2048,2048,64,128,S128);
    mp.gos=map2d(fn,go,2048,2048,32,128,CU_TENSOR_MAP_SWIZZLE_64B);
    mp.woa=map2d(fn,d_in[3],1024,1024,64,64,S128);
    { cuuint64_t d[4]={1024,32,4,8}, s[3]={2048,65536,262144}; cuuint32_t b[4]={64,32,1,2}; mp.wob=mk_map(fn,d_in[6],4,d,s,b,S128); }
    mp.out=map2d(fn,d_out,1024,2048,64,128,S128);
    mp.wphi=map2d(fn,d_in[2],32,1024,32,128,CU_TENSOR_MAP_SWIZZLE_64B);
    mp.xp=(const bf16*)d_in[0]; mp.gw=(const bf16*)d_in[7];
    cudaFuncSetAttribute(k_main,cudaFuncAttributeMaxDynamicSharedMemorySize,k2::SMEM);
    for(int i=0;i<8;i++) key[i]=cur[i];
    init=true;
  }
  cudaLaunchConfig_t cfg={}; cfg.gridDim=128; cfg.blockDim=512; cfg.dynamicSmemBytes=k2::SMEM; cfg.stream=cudaStreamPerThread;
  cudaLaunchAttribute at[1];
  at[0].id=cudaLaunchAttributeClusterDimension; at[0].val.clusterDim.x=2; at[0].val.clusterDim.y=1; at[0].val.clusterDim.z=1;
  cfg.attrs=at; cfg.numAttrs=1;
  cudaLaunchKernelEx(&cfg,k_main,mp);
}
```
